```python
import torch

def _softmax(x, axis=-1):
    return torch.softmax(x, dim=axis)
def _gelu(x):
    return torch.nn.functional.gelu(x, approximate="tanh")
def _silu(x):
    return torch.nn.functional.silu(x)
def _sigmoid(x):
    return torch.sigmoid(x)
def _layernorm(x, axis=-1, eps=1e-5):
    m = x.mean(dim=axis, keepdim=True)
    v = x.var(dim=axis, keepdim=True, unbiased=False)
    return (x - m) / torch.sqrt(v + eps)
def _scatter_add(tgt, idx, src, axis=0):
    return tgt.clone().index_add_(axis, idx, src)
def _segment_sum(src, seg, n):
    out = torch.zeros((n,) + src.shape[1:], dtype=src.dtype)
    return out.index_add_(0, seg, src)
def _pad(x, pw):
    flat = tuple(v for pair in reversed(pw) for v in pair)
    return torch.nn.functional.pad(x, flat)

kernel_name = 'gated_mix__spectral_gfnet__mixer_token_mlp__prompt'

def setup_inputs():

    _w = (lambda a: (lambda t: t.to(torch.bfloat16) if t.is_floating_point() else t)(torch.as_tensor(a)))
    def _A_setup():
        B, S, D = 1, 2048, 576
        Df = D // 2 + 1
        return {
            "x": _w((lambda *s: torch.randn(*s, dtype=torch.bfloat16) * 0.05)(B, S, D)),
            "w_r": _w((lambda *s: torch.randn(*s, dtype=torch.bfloat16) * 1.6)(S, Df) * 0.02),
            "w_i": _w((lambda *s: torch.randn(*s, dtype=torch.bfloat16) * 1.6)(S, Df) * 0.02),
        }
    _A_in = _A_setup()

    def _B_setup():
        B, S, D, F = 1, 2048, 576, 4608
        return {
            "x": _w((lambda *s: torch.randn(*s, dtype=torch.bfloat16) * 0.05)(B, S, D)),
            "w1": _w((lambda *s: torch.randn(*s, dtype=torch.bfloat16) * 0.2)(S, F) * (S ** -0.5)),
            "b1": _w((lambda *s: torch.randn(*s, dtype=torch.bfloat16) * 3.2)(F) * 0.02),
            "w2": _w((lambda *s: torch.randn(*s, dtype=torch.bfloat16) * 0.05)(F, S) * (F ** -0.5)),
            "b2": _w((lambda *s: torch.randn(*s, dtype=torch.bfloat16) * 0.1)(S) * 0.02),
        }
    _B_in = _B_setup()

    return {
        "A_x": _A_in["x"],
        "A_w_r": _A_in["w_r"],
        "A_w_i": _A_in["w_i"],
        "B_x": _B_in["x"],
        "B_w1": _B_in["w1"],
        "B_b1": _B_in["b1"],
        "B_w2": _B_in["w2"],
        "B_b2": _B_in["b2"],
        "gate_w": _w((lambda *s: torch.randn(*s, dtype=torch.bfloat16) * 0.05)(576) * 16.0),
    }

def reference(A_x, A_w_r, A_w_i, B_x, B_w1, B_b1, B_w2, B_b2, gate_w):
    def _A_ref(x, w_r, w_i):
        B, S, D = x.shape
        X = (lambda x, axes=(-2,-1): torch.fft.rfft2(x.float(), dim=axes))(x, axes=(-2, -1))
        W = w_r + 1j * w_i
        X = X * W
        y = (lambda x, s, axes=(-2,-1): torch.fft.irfft2(x, s=s, dim=axes).to(torch.bfloat16))(X, (S, D), axes=(-2, -1))
        return y

    def _B_ref(x, w1, b1, w2, b2):
        B, S, D = x.shape
        h = _layernorm(x, axis=-1)
        u = torch.einsum("bsd,sf->bdf", h, w1) + b1
        u = _gelu(u)
        y = torch.einsum("bdf,fs->bds", u, w2) + b2
        return (lambda x, *d: x.permute(*d))(y, 0, 2, 1)

    x = A_x
    g = _sigmoid((x * gate_w).sum(-1, keepdims=True))
    a = _A_ref(x, A_w_r, A_w_i)
    b = _B_ref(x, B_w1, B_b1, B_w2, B_b2)
    return g * a + (1 - g) * b
```

```cpp
#include <cuda_runtime.h>
#include <cuda_bf16.h>
#include <cuda.h>
#include <stdint.h>

template<int TA, int TB> __device__ __forceinline__ void wg_ss_n192(float (&d)[96], uint64_t da, uint64_t db, int sd) {
  asm volatile("{\n.reg .pred p;\nsetp.ne.b32 p, %98, 0;\n"
    "wgmma.mma_async.sync.aligned.m64n192k16.f32.bf16.bf16 {%0, %1, %2, %3, %4, %5, %6, %7, %8, %9, %10, %11, %12, %13, %14, %15, %16, %17, %18, %19, %20, %21, %22, %23, %24, %25, %26, %27, %28, %29, %30, %31, %32, %33, %34, %35, %36, %37, %38, %39, %40, %41, %42, %43, %44, %45, %46, %47, %48, %49, %50, %51, %52, %53, %54, %55, %56, %57, %58, %59, %60, %61, %62, %63, %64, %65, %66, %67, %68, %69, %70, %71, %72, %73, %74, %75, %76, %77, %78, %79, %80, %81, %82, %83, %84, %85, %86, %87, %88, %89, %90, %91, %92, %93, %94, %95}, %96, %97, p, 1, 1, %99, %100;\n}\n"
    : "+f"(d[0]), "+f"(d[1]), "+f"(d[2]), "+f"(d[3]), "+f"(d[4]), "+f"(d[5]), "+f"(d[6]), "+f"(d[7]), "+f"(d[8]), "+f"(d[9]), "+f"(d[10]), "+f"(d[11]), "+f"(d[12]), "+f"(d[13]), "+f"(d[14]), "+f"(d[15]), "+f"(d[16]), "+f"(d[17]), "+f"(d[18]), "+f"(d[19]), "+f"(d[20]), "+f"(d[21]), "+f"(d[22]), "+f"(d[23]), "+f"(d[24]), "+f"(d[25]), "+f"(d[26]), "+f"(d[27]), "+f"(d[28]), "+f"(d[29]), "+f"(d[30]), "+f"(d[31]), "+f"(d[32]), "+f"(d[33]), "+f"(d[34]), "+f"(d[35]), "+f"(d[36]), "+f"(d[37]), "+f"(d[38]), "+f"(d[39]), "+f"(d[40]), "+f"(d[41]), "+f"(d[42]), "+f"(d[43]), "+f"(d[44]), "+f"(d[45]), "+f"(d[46]), "+f"(d[47]), "+f"(d[48]), "+f"(d[49]), "+f"(d[50]), "+f"(d[51]), "+f"(d[52]), "+f"(d[53]), "+f"(d[54]), "+f"(d[55]), "+f"(d[56]), "+f"(d[57]), "+f"(d[58]), "+f"(d[59]), "+f"(d[60]), "+f"(d[61]), "+f"(d[62]), "+f"(d[63]), "+f"(d[64]), "+f"(d[65]), "+f"(d[66]), "+f"(d[67]), "+f"(d[68]), "+f"(d[69]), "+f"(d[70]), "+f"(d[71]), "+f"(d[72]), "+f"(d[73]), "+f"(d[74]), "+f"(d[75]), "+f"(d[76]), "+f"(d[77]), "+f"(d[78]), "+f"(d[79]), "+f"(d[80]), "+f"(d[81]), "+f"(d[82]), "+f"(d[83]), "+f"(d[84]), "+f"(d[85]), "+f"(d[86]), "+f"(d[87]), "+f"(d[88]), "+f"(d[89]), "+f"(d[90]), "+f"(d[91]), "+f"(d[92]), "+f"(d[93]), "+f"(d[94]), "+f"(d[95])
    : "l"(da), "l"(db), "r"(sd), "n"(TA), "n"(TB));
}

template<int TA, int TB> __device__ __forceinline__ void wg_ss_n96(float (&d)[48], uint64_t da, uint64_t db, int sd) {
  asm volatile("{\n.reg .pred p;\nsetp.ne.b32 p, %50, 0;\n"
    "wgmma.mma_async.sync.aligned.m64n96k16.f32.bf16.bf16 {%0, %1, %2, %3, %4, %5, %6, %7, %8, %9, %10, %11, %12, %13, %14, %15, %16, %17, %18, %19, %20, %21, %22, %23, %24, %25, %26, %27, %28, %29, %30, %31, %32, %33, %34, %35, %36, %37, %38, %39, %40, %41, %42, %43, %44, %45, %46, %47}, %48, %49, p, 1, 1, %51, %52;\n}\n"
    : "+f"(d[0]), "+f"(d[1]), "+f"(d[2]), "+f"(d[3]), "+f"(d[4]), "+f"(d[5]), "+f"(d[6]), "+f"(d[7]), "+f"(d[8]), "+f"(d[9]), "+f"(d[10]), "+f"(d[11]), "+f"(d[12]), "+f"(d[13]), "+f"(d[14]), "+f"(d[15]), "+f"(d[16]), "+f"(d[17]), "+f"(d[18]), "+f"(d[19]), "+f"(d[20]), "+f"(d[21]), "+f"(d[22]), "+f"(d[23]), "+f"(d[24]), "+f"(d[25]), "+f"(d[26]), "+f"(d[27]), "+f"(d[28]), "+f"(d[29]), "+f"(d[30]), "+f"(d[31]), "+f"(d[32]), "+f"(d[33]), "+f"(d[34]), "+f"(d[35]), "+f"(d[36]), "+f"(d[37]), "+f"(d[38]), "+f"(d[39]), "+f"(d[40]), "+f"(d[41]), "+f"(d[42]), "+f"(d[43]), "+f"(d[44]), "+f"(d[45]), "+f"(d[46]), "+f"(d[47])
    : "l"(da), "l"(db), "r"(sd), "n"(TA), "n"(TB));
}

template<int TB> __device__ __forceinline__ void wg_rs_n192(float (&d)[96], uint32_t a0, uint32_t a1, uint32_t a2, uint32_t a3, uint64_t db, int sd) {
  asm volatile("{\n.reg .pred p;\nsetp.ne.b32 p, %101, 0;\n"
    "wgmma.mma_async.sync.aligned.m64n192k16.f32.bf16.bf16 {%0, %1, %2, %3, %4, %5, %6, %7, %8, %9, %10, %11, %12, %13, %14, %15, %16, %17, %18, %19, %20, %21, %22, %23, %24, %25, %26, %27, %28, %29, %30, %31, %32, %33, %34, %35, %36, %37, %38, %39, %40, %41, %42, %43, %44, %45, %46, %47, %48, %49, %50, %51, %52, %53, %54, %55, %56, %57, %58, %59, %60, %61, %62, %63, %64, %65, %66, %67, %68, %69, %70, %71, %72, %73, %74, %75, %76, %77, %78, %79, %80, %81, %82, %83, %84, %85, %86, %87, %88, %89, %90, %91, %92, %93, %94, %95}, {%96, %97, %98, %99}, %100, p, 1, 1, %102;\n}\n"
    : "+f"(d[0]), "+f"(d[1]), "+f"(d[2]), "+f"(d[3]), "+f"(d[4]), "+f"(d[5]), "+f"(d[6]), "+f"(d[7]), "+f"(d[8]), "+f"(d[9]), "+f"(d[10]), "+f"(d[11]), "+f"(d[12]), "+f"(d[13]), "+f"(d[14]), "+f"(d[15]), "+f"(d[16]), "+f"(d[17]), "+f"(d[18]), "+f"(d[19]), "+f"(d[20]), "+f"(d[21]), "+f"(d[22]), "+f"(d[23]), "+f"(d[24]), "+f"(d[25]), "+f"(d[26]), "+f"(d[27]), "+f"(d[28]), "+f"(d[29]), "+f"(d[30]), "+f"(d[31]), "+f"(d[32]), "+f"(d[33]), "+f"(d[34]), "+f"(d[35]), "+f"(d[36]), "+f"(d[37]), "+f"(d[38]), "+f"(d[39]), "+f"(d[40]), "+f"(d[41]), "+f"(d[42]), "+f"(d[43]), "+f"(d[44]), "+f"(d[45]), "+f"(d[46]), "+f"(d[47]), "+f"(d[48]), "+f"(d[49]), "+f"(d[50]), "+f"(d[51]), "+f"(d[52]), "+f"(d[53]), "+f"(d[54]), "+f"(d[55]), "+f"(d[56]), "+f"(d[57]), "+f"(d[58]), "+f"(d[59]), "+f"(d[60]), "+f"(d[61]), "+f"(d[62]), "+f"(d[63]), "+f"(d[64]), "+f"(d[65]), "+f"(d[66]), "+f"(d[67]), "+f"(d[68]), "+f"(d[69]), "+f"(d[70]), "+f"(d[71]), "+f"(d[72]), "+f"(d[73]), "+f"(d[74]), "+f"(d[75]), "+f"(d[76]), "+f"(d[77]), "+f"(d[78]), "+f"(d[79]), "+f"(d[80]), "+f"(d[81]), "+f"(d[82]), "+f"(d[83]), "+f"(d[84]), "+f"(d[85]), "+f"(d[86]), "+f"(d[87]), "+f"(d[88]), "+f"(d[89]), "+f"(d[90]), "+f"(d[91]), "+f"(d[92]), "+f"(d[93]), "+f"(d[94]), "+f"(d[95])
    : "r"(a0), "r"(a1), "r"(a2), "r"(a3), "l"(db), "r"(sd), "n"(TB));
}

template<int TB> __device__ __forceinline__ void wg_rs_n128(float (&d)[64], uint32_t a0, uint32_t a1, uint32_t a2, uint32_t a3, uint64_t db, int sd) {
  asm volatile("{\n.reg .pred p;\nsetp.ne.b32 p, %69, 0;\n"
    "wgmma.mma_async.sync.aligned.m64n128k16.f32.bf16.bf16 {%0, %1, %2, %3, %4, %5, %6, %7, %8, %9, %10, %11, %12, %13, %14, %15, %16, %17, %18, %19, %20, %21, %22, %23, %24, %25, %26, %27, %28, %29, %30, %31, %32, %33, %34, %35, %36, %37, %38, %39, %40, %41, %42, %43, %44, %45, %46, %47, %48, %49, %50, %51, %52, %53, %54, %55, %56, %57, %58, %59, %60, %61, %62, %63}, {%64, %65, %66, %67}, %68, p, 1, 1, %70;\n}\n"
    : "+f"(d[0]), "+f"(d[1]), "+f"(d[2]), "+f"(d[3]), "+f"(d[4]), "+f"(d[5]), "+f"(d[6]), "+f"(d[7]), "+f"(d[8]), "+f"(d[9]), "+f"(d[10]), "+f"(d[11]), "+f"(d[12]), "+f"(d[13]), "+f"(d[14]), "+f"(d[15]), "+f"(d[16]), "+f"(d[17]), "+f"(d[18]), "+f"(d[19]), "+f"(d[20]), "+f"(d[21]), "+f"(d[22]), "+f"(d[23]), "+f"(d[24]), "+f"(d[25]), "+f"(d[26]), "+f"(d[27]), "+f"(d[28]), "+f"(d[29]), "+f"(d[30]), "+f"(d[31]), "+f"(d[32]), "+f"(d[33]), "+f"(d[34]), "+f"(d[35]), "+f"(d[36]), "+f"(d[37]), "+f"(d[38]), "+f"(d[39]), "+f"(d[40]), "+f"(d[41]), "+f"(d[42]), "+f"(d[43]), "+f"(d[44]), "+f"(d[45]), "+f"(d[46]), "+f"(d[47]), "+f"(d[48]), "+f"(d[49]), "+f"(d[50]), "+f"(d[51]), "+f"(d[52]), "+f"(d[53]), "+f"(d[54]), "+f"(d[55]), "+f"(d[56]), "+f"(d[57]), "+f"(d[58]), "+f"(d[59]), "+f"(d[60]), "+f"(d[61]), "+f"(d[62]), "+f"(d[63])
    : "r"(a0), "r"(a1), "r"(a2), "r"(a3), "l"(db), "r"(sd), "n"(TB));
}

namespace {

typedef __nv_bfloat16 bf16;

constexpr int S_ = 2048, D_ = 576, F_ = 4608, DF_ = 289;
constexpr int NCTA = 132, NG = 108, NTHREADS = 384;

constexpr uint32_t STAGE_BYTES = 40960;
constexpr uint32_t SM_STG = 163840;
constexpr uint32_t SM_SIDE = 212992;
constexpr uint32_t SM_BAR = 231680;
constexpr uint32_t SM_TOTAL = 232448;
constexpr uint32_t B_FULL = SM_BAR, B_EMPTY = SM_BAR + 32, B_X = SM_BAR + 64, B_PFREE = SM_BAR + 72, B_LFREE = SM_BAR + 80,
                   B_W = SM_BAR + 88, B_AUX = SM_BAR + 96, B_F2 = SM_BAR + 104  , SM_EPOCH = SM_BAR + 144;

constexpr int FL_H = 0, FL_U = 32, FL_XB = 140, FL_TF = 156, FL_WT = 157, FL_X1 = 158, FL_Z = 159, FL_A = 160, NFLAGS = 208;

struct Params {
  CUtensorMap tW1, tH, tW2, tU, tOut, tXB, tTFk, tX1s, tX1c, tZc, tZT, tTFn;
  const bf16 *Ax, *Wr, *Wi, *b1, *b2, *gw;
};

}

__device__ __align__(1024) bf16 g_h[S_ * D_];
__device__ __align__(1024) bf16 g_u[F_ * D_];
__device__ __align__(1024) bf16 g_xb[S_ * D_];
__device__ __align__(1024) bf16 g_TF[576 * 288];
__device__ __align__(1024) bf16 g_X1T[576 * S_];
__device__ __align__(1024) bf16 g_ZT[576 * S_];
__device__ __align__(1024) uint32_t g_Wt[288 * 2048];
__device__ __align__(1024) uint4 g_afrag[16 * 6 * 6 * 256];
__device__ __align__(1024) float4 g_UV[2048];
__device__ __align__(1024) float g_gate[S_];
__device__ __align__(1024) unsigned g_flags[NFLAGS * 32];
__device__ __align__(1024) unsigned g_epoch[NCTA * 32];

#define STAMP(i) do { } while (0)

namespace {

constexpr long long TIMEOUT_CYC = 400000000LL;

__device__ __forceinline__ bool on_timeout(int site) {
  __trap();
  return true;
}
__device__ __forceinline__ bool aborted() {
  return false;
}

__device__ __forceinline__ uint32_t smem_u32(const void* p) { return (uint32_t)__cvta_generic_to_shared(p); }
__device__ __forceinline__ void mbar_init(uint32_t bar, uint32_t cnt) { asm volatile("mbarrier.init.shared::cta.b64 [%0], %1;" ::"r"(bar), "r"(cnt) : "memory"); }
__device__ __forceinline__ void mbar_expect_tx(uint32_t bar, uint32_t bytes) { asm volatile("mbarrier.arrive.expect_tx.shared::cta.b64 _, [%0], %1;" ::"r"(bar), "r"(bytes) : "memory"); }
__device__ __forceinline__ void mbar_arrive(uint32_t bar) { asm volatile("mbarrier.arrive.shared::cta.b64 _, [%0];" ::"r"(bar) : "memory"); }
__device__ __forceinline__ uint32_t mapa(uint32_t addr, uint32_t cta) {
  uint32_t r; asm("mapa.shared::cluster.u32 %0, %1, %2;" : "=r"(r) : "r"(addr), "r"(cta)); return r;
}
__device__ __forceinline__ void mbar_arrive_remote(uint32_t raddr) { asm volatile("mbarrier.arrive.release.cluster.shared::cluster.b64 _, [%0];" ::"r"(raddr) : "memory"); }
__device__ __forceinline__ bool mbar_try(uint32_t bar, uint32_t parity) {
  uint32_t ok;
  asm volatile("{\n.reg .pred p;\nmbarrier.try_wait.parity.shared::cta.b64 p, [%1], %2;\nselp.u32 %0, 1, 0, p;\n}" : "=r"(ok) : "r"(bar), "r"(parity) : "memory");
  return ok != 0;
}
__device__ __forceinline__ bool mbar_try_cl(uint32_t bar, uint32_t parity) {
  uint32_t ok;
  asm volatile("{\n.reg .pred p;\nmbarrier.try_wait.parity.acquire.cluster.shared::cta.b64 p, [%1], %2;\nselp.u32 %0, 1, 0, p;\n}" : "=r"(ok) : "r"(bar), "r"(parity) : "memory");
  return ok != 0;
}
__device__ __forceinline__ void mbar_wait_slow(uint32_t bar, uint32_t parity, int site, int cl) {
  long long t0 = clock64();
  while (!(cl ? mbar_try_cl(bar, parity) : mbar_try(bar, parity))) {
    if (clock64() - t0 > TIMEOUT_CYC) { on_timeout(site); return; }
    if (aborted()) return;
  }
}
__device__ __forceinline__ void mbar_wait(uint32_t bar, uint32_t parity, int site) {
  if (!mbar_try(bar, parity)) { if (!mbar_try(bar, parity)) mbar_wait_slow(bar, parity, site, 0); }
}
__device__ __forceinline__ void mbar_wait_cl(uint32_t bar, uint32_t parity, int site) {
  if (!mbar_try_cl(bar, parity)) mbar_wait_slow(bar, parity, site, 1);
}
__device__ __forceinline__ unsigned ld_acquire(const unsigned* p) {
  unsigned v; asm volatile("ld.acquire.gpu.global.u32 %0, [%1];" : "=r"(v) : "l"(p) : "memory"); return v;
}
__device__ __forceinline__ void red_release(unsigned* p, unsigned v) { asm volatile("red.release.gpu.global.add.u32 [%0], %1;" ::"l"(p), "r"(v) : "memory"); }
__device__ __forceinline__ void fence_async_all() { asm volatile("fence.proxy.async;" ::: "memory"); }
__device__ __forceinline__ void fence_async_smem() { asm volatile("fence.proxy.async.shared::cta;" ::: "memory"); }
__device__ __forceinline__ void wait_flag(int idx, unsigned target, int site) {
  const unsigned* p = g_flags + idx * 32;
  if ((int)(ld_acquire(p) - target) >= 0) return;
  long long t0 = clock64();
  while ((int)(ld_acquire(p) - target) < 0) {
    if (clock64() - t0 > TIMEOUT_CYC) { on_timeout(site); return; }
    if (aborted()) return;
  }
}
__device__ __forceinline__ uint32_t poll_mask(int idx0, int n, unsigned target, int need, int site) {
  const int lane = threadIdx.x & 31;
  const unsigned* p = g_flags + (idx0 + (lane < n ? lane : 0)) * 32;
  long long t0 = clock64();
  uint32_t m;
  while (true) {
    unsigned v = ld_acquire(p);
    m = __ballot_sync(0xffffffffu, (int)(v - target) >= 0);
    if ((m >> need) & 1) break;
    bool bail = (clock64() - t0 > TIMEOUT_CYC) || aborted();
    if (__any_sync(0xffffffffu, bail)) { on_timeout(site); m = 0xffffffffu; break; }
  }
  fence_async_all();
  return m;
}

__device__ __forceinline__ void tma2d(uint32_t dst, const CUtensorMap* m, int c0, int c1, uint32_t bar) {
  asm volatile("cp.async.bulk.tensor.2d.shared::cluster.global.mbarrier::complete_tx::bytes [%0], [%1, {%3, %4}], [%2];"
               ::"r"(dst), "l"(m), "r"(bar), "r"(c0), "r"(c1) : "memory");
}
__device__ __forceinline__ void tma3d(uint32_t dst, const CUtensorMap* m, int c0, int c1, int c2, uint32_t bar) {
  asm volatile("cp.async.bulk.tensor.3d.shared::cluster.global.mbarrier::complete_tx::bytes [%0], [%1, {%3, %4, %5}], [%2];"
               ::"r"(dst), "l"(m), "r"(bar), "r"(c0), "r"(c1), "r"(c2) : "memory");
}
__device__ __forceinline__ void tma2d_st(const CUtensorMap* m, uint32_t src, int c0, int c1) {
  asm volatile("cp.async.bulk.tensor.2d.global.shared::cta.bulk_group [%0, {%2, %3}], [%1];" ::"l"(m), "r"(src), "r"(c0), "r"(c1) : "memory");
}
__device__ __forceinline__ void tma3d_st(const CUtensorMap* m, uint32_t src, int c0, int c1, int c2) {
  asm volatile("cp.async.bulk.tensor.3d.global.shared::cta.bulk_group [%0, {%2, %3, %4}], [%1];" ::"l"(m), "r"(src), "r"(c0), "r"(c1), "r"(c2) : "memory");
}
__device__ __forceinline__ void bulk_ld(uint32_t dst, const void* src, uint32_t bytes, uint32_t bar) {
  asm volatile("cp.async.bulk.shared::cluster.global.mbarrier::complete_tx::bytes [%0], [%1], %2, [%3];" ::"r"(dst), "l"(src), "r"(bytes), "r"(bar) : "memory");
}
__device__ __forceinline__ void bulk_commit() { asm volatile("cp.async.bulk.commit_group;" ::: "memory"); }
__device__ __forceinline__ void bulk_wait0() { asm volatile("cp.async.bulk.wait_group 0;" ::: "memory"); }
__device__ __forceinline__ void bulk_wait0_read() { asm volatile("cp.async.bulk.wait_group.read 0;" ::: "memory"); }
__device__ __forceinline__ void prefetch_map(const CUtensorMap* m) { asm volatile("prefetch.tensormap [%0];" ::"l"(m) : "memory"); }

__device__ __forceinline__ uint64_t mkdesc(uint32_t addr, uint32_t lbo, uint32_t sbo) {
  return (uint64_t)((addr & 0x3FFFF) >> 4) | ((uint64_t)(lbo >> 4) << 16) | ((uint64_t)(sbo >> 4) << 32) | (1ull << 62);
}
__device__ __forceinline__ void wg_fence() { asm volatile("wgmma.fence.sync.aligned;" ::: "memory"); }
__device__ __forceinline__ void wg_commit() { asm volatile("wgmma.commit_group.sync.aligned;" ::: "memory"); }
template <int N> __device__ __forceinline__ void wg_wait() { asm volatile("wgmma.wait_group.sync.aligned %0;" ::"n"(N) : "memory"); }
__device__ __forceinline__ void bar_sync(int id, int n) { asm volatile("bar.sync %0, %1;" ::"r"(id), "r"(n) : "memory"); }

__device__ __forceinline__ uint32_t pack2(float lo, float hi) {
  uint32_t r; asm("cvt.rn.bf16x2.f32 %0, %1, %2;" : "=r"(r) : "f"(hi), "f"(lo)); return r;
}
__device__ __forceinline__ float bf_lo(uint32_t v) { return __uint_as_float(v << 16); }
__device__ __forceinline__ float bf_hi(uint32_t v) { return __uint_as_float(v & 0xffff0000u); }
__device__ __forceinline__ float bfr(float x) { return __bfloat162float(__float2bfloat16_rn(x)); }
__device__ __forceinline__ void stsm4(uint32_t addr, uint32_t a, uint32_t b, uint32_t c, uint32_t d) {
  asm volatile("stmatrix.sync.aligned.m8n8.x4.shared.b16 [%0], {%1, %2, %3, %4};" ::"r"(addr), "r"(a), "r"(b), "r"(c), "r"(d) : "memory");
}
__device__ __forceinline__ void stsm4t(uint32_t addr, uint32_t a, uint32_t b, uint32_t c, uint32_t d) {
  asm volatile("stmatrix.sync.aligned.m8n8.x4.trans.shared.b16 [%0], {%1, %2, %3, %4};" ::"r"(addr), "r"(a), "r"(b), "r"(c), "r"(d) : "memory");
}
__device__ __forceinline__ float gelu_tanh(float x) {
  float x2 = x * x;
  float z = x * fmaf(x2, 0.044715f * 0.7978845608028654f, 0.7978845608028654f);
  float t; asm("tanh.approx.f32 %0, %1;" : "=f"(t) : "f"(z));
  float hx = 0.5f * x;
  return fmaf(hx, t, hx);
}

__device__ __forceinline__ float warp_sum(float v) {
#pragma unroll
  for (int o = 16; o > 0; o >>= 1) v += __shfl_xor_sync(0xffffffffu, v, o);
  return v;
}

__device__ __forceinline__ void row_job(const Params& P, int row0, int lane) {
  uint32_t lo[2][5], hi[2][5];
  const bool ok4 = lane < 16;
#pragma unroll
  for (int r = 0; r < 2; r++) {
    const uint32_t* x = reinterpret_cast<const uint32_t*>(P.Ax + (size_t)(row0 + r) * D_);
#pragma unroll
    for (int i = 0; i < 5; i++) {
      lo[r][i] = (i < 4 || ok4) ? __ldg(x + lane + 32 * i) : 0u;
      hi[r][i] = (i < 4 || ok4) ? __ldg(x + 144 + lane + 32 * i) : 0u;
    }
  }
  uint32_t gl[5], gh[5];
  {
    const uint32_t* gw = reinterpret_cast<const uint32_t*>(P.gw);
#pragma unroll
    for (int i = 0; i < 5; i++) {
      gl[i] = (i < 4 || ok4) ? __ldg(gw + lane + 32 * i) : 0u;
      gh[i] = (i < 4 || ok4) ? __ldg(gw + 144 + lane + 32 * i) : 0u;
    }
  }
  float s[2];
#pragma unroll
  for (int r = 0; r < 2; r++) {
    float a = 0.f;
#pragma unroll
    for (int i = 0; i < 5; i++) a += (bf_lo(lo[r][i]) + bf_hi(lo[r][i])) + (bf_lo(hi[r][i]) + bf_hi(hi[r][i]));
    s[r] = a;
  }
#pragma unroll
  for (int o = 16; o > 0; o >>= 1) { s[0] += __shfl_xor_sync(0xffffffffu, s[0], o); s[1] += __shfl_xor_sync(0xffffffffu, s[1], o); }
  float mean[2], q[2];
#pragma unroll
  for (int r = 0; r < 2; r++) {
    mean[r] = s[r] * (1.0f / 576.0f);
    float a = 0.f;
#pragma unroll
    for (int i = 0; i < 5; i++) {
      float d0 = bf_lo(lo[r][i]) - mean[r], d1 = bf_hi(lo[r][i]) - mean[r], d2 = bf_lo(hi[r][i]) - mean[r], d3 = bf_hi(hi[r][i]) - mean[r];
      float t = fmaf(d0, d0, d1 * d1) + fmaf(d2, d2, d3 * d3);
      a += (i < 4 || ok4) ? t : 0.f;
    }
    q[r] = a;
  }
#pragma unroll
  for (int o = 16; o > 0; o >>= 1) { q[0] += __shfl_xor_sync(0xffffffffu, q[0], o); q[1] += __shfl_xor_sync(0xffffffffu, q[1], o); }
#pragma unroll
  for (int r = 0; r < 2; r++) {
    const float mb = bfr(mean[r]);
    const float sd = bfr(sqrtf(bfr(bfr(q[r] * (1.0f / 576.0f)) + 1e-5f)));
    const float rs = 1.0f / sd;
    uint32_t* h = reinterpret_cast<uint32_t*>(g_h + (size_t)(row0 + r) * D_);
#pragma unroll
    for (int i = 0; i < 5; i++) {
      if (i < 4 || ok4) {
        h[lane + 32 * i] = pack2(bfr(bf_lo(lo[r][i]) - mb) * rs, bfr(bf_hi(lo[r][i]) - mb) * rs);
        h[144 + lane + 32 * i] = pack2(bfr(bf_lo(hi[r][i]) - mb) * rs, bfr(bf_hi(hi[r][i]) - mb) * rs);
      }
    }
  }
  fence_async_all();
  __syncwarp();
  if (lane == 0) red_release(g_flags + (FL_H + (row0 >> 6)) * 32, 1u);
  float z[2];
#pragma unroll
  for (int r = 0; r < 2; r++) {
    uint32_t* xb = reinterpret_cast<uint32_t*>(g_xb + (size_t)(row0 + r) * D_);
    float a = 0.f;
#pragma unroll
    for (int i = 0; i < 5; i++) {
      const float l0 = bf_lo(lo[r][i]), l1 = bf_hi(lo[r][i]), h0 = bf_lo(hi[r][i]), h1 = bf_hi(hi[r][i]);
      a += (bfr(l0 * bf_lo(gl[i])) + bfr(l1 * bf_hi(gl[i]))) + (bfr(h0 * bf_lo(gh[i])) + bfr(h1 * bf_hi(gh[i])));
      if (i < 4 || ok4) {
        xb[lane + 32 * i] = pack2(l0 + h0, l1 + h1);
        xb[144 + lane + 32 * i] = pack2(l0 - h0, l1 - h1);
      }
    }
    z[r] = a;
  }
#pragma unroll
  for (int o = 16; o > 0; o >>= 1) { z[0] += __shfl_xor_sync(0xffffffffu, z[0], o); z[1] += __shfl_xor_sync(0xffffffffu, z[1], o); }
  if (lane < 2) g_gate[row0 + lane] = bfr(1.0f / (1.0f + __expf(-bfr(lane ? z[1] : z[0]))));
  fence_async_all();
  __syncwarp();
  if (lane == 0) red_release(g_flags + (FL_XB + (row0 >> 7)) * 32, 1u);
}

__device__ __forceinline__ void w_job(uint32_t sb, int cta, int t3, int lane) {
  mbar_wait(sb + B_W, 0, 1);
  const int w = cta & 3, jp = cta >> 2;
  const uint32_t base = sb + SM_SIDE;
#pragma unroll 2
  for (int it = 0; it < 12; it++) {
    int idx = t3 + 96 * it;
    int ip = idx & 3, cc = idx >> 2;
    int k = cc < 144 ? 2 * cc : 2 * (cc - 144) + 1;
    uint32_t o[4];
#pragma unroll
    for (int ii = 0; ii < 2; ii++) {
#pragma unroll
      for (int e = 0; e < 2; e++) {
        uint32_t off = base + e * 4624 + ((2 * ip + ii) * DF_ + k) * 2;
        uint16_t wr, wi;
        asm volatile("ld.shared.u16 %0, [%1];" : "=h"(wr) : "r"(off));
        asm volatile("ld.shared.u16 %0, [%1];" : "=h"(wi) : "r"(off + 9248));
        o[ii * 2 + e] = (uint32_t)wr | ((uint32_t)wi << 16);
      }
    }
    uint4* dst = reinterpret_cast<uint4*>(g_Wt + (size_t)cc * 2048 + (jp * 32 + 8 * w + 2 * ip) * 2);
    *dst = make_uint4(o[0], o[1], o[2], o[3]);
  }
  __syncwarp();
  if (lane == 0) { red_release(g_flags + FL_WT * 32, 1u); mbar_arrive(sb + B_AUX); }
}

__device__ __forceinline__ void tf_gen(int gt  , int lane) {
#pragma unroll 1
  for (int idx = gt; idx < 576 * 144; idx += 6144) {
    int kr = idx / 144, d = 2 * (idx - kr * 144);
    int k = kr < 288 ? (kr & ~1) : (((kr - 288) & ~1) + 1);
    int m0 = (d * k) % 576, m1 = m0 + k;
    if (m1 >= 576) m1 -= 576;
    if (kr == 1) { m0 = 0; m1 = 288; }
    float v0, v1;
    if ((kr & 1) == 0 || kr == 1) { v0 = cospif(m0 * (1.0f / 288.0f)); v1 = cospif(m1 * (1.0f / 288.0f)); }
    else { v0 = -sinpif(m0 * (1.0f / 288.0f)); v1 = -sinpif(m1 * (1.0f / 288.0f)); }
    reinterpret_cast<uint32_t*>(g_TF)[idx] = pack2(v0, v1);
  }
  fence_async_all();
  __syncwarp();
  if (lane == 0) red_release(g_flags + FL_TF * 32, 1u);
}

__global__ void __launch_bounds__(NTHREADS, 1) mega_kernel(const __grid_constant__ Params P) {
  extern __shared__ __align__(1024) uint8_t smem_raw[];
  const uint32_t sb = smem_u32(smem_raw);
  const int tid = threadIdx.x, warp = tid >> 5, lane = tid & 31;
  const int cta = blockIdx.x;
  const uint32_t rank = cta & 1;
  if (tid == 0) {
    if (sb & 1023u) __trap();
    unsigned e = g_epoch[cta * 32];
    g_epoch[cta * 32] = e + 1;
    asm volatile("st.shared.u32 [%0], %1;" ::"r"(sb + SM_EPOCH), "r"(e) : "memory");
    for (int i = 0; i < 4; i++) { mbar_init(sb + B_FULL + 8 * i, 1); mbar_init(sb + B_EMPTY + 8 * i, 8); }
    mbar_init(sb + B_X, 1); mbar_init(sb + B_PFREE, 1); mbar_init(sb + B_LFREE, 8);
    mbar_init(sb + B_W, 1); mbar_init(sb + B_AUX, 3);
    for (int i = 0; i < 4; i++) mbar_init(sb + B_F2 + 8 * i, 1);
    mbar_expect_tx(sb + B_X, 49152);
    asm volatile("fence.mbarrier_init.release.cluster;" ::: "memory");
  }
  __syncthreads();
  asm volatile("barrier.cluster.arrive.release.aligned;" ::: "memory");
  unsigned epoch;
  asm volatile("ld.shared.u32 %0, [%1];" : "=r"(epoch) : "r"(sb + SM_EPOCH));
  const unsigned ep1 = epoch + 1;

  const bool isG = cta < NG;
  const int cl = cta >> 1;
  const int gj = cl / 18, gp = cl % 18;
  const int fc = cta - NG;

  if (warp < 4) {
    asm volatile("setmaxnreg.dec.sync.aligned.u32 56;");
    if (warp == 0) {
      uint32_t st = 0, ph = 1;
      if (isG) {
        if (lane == 0) { prefetch_map(&P.tW1); prefetch_map(&P.tH); prefetch_map(&P.tW2); prefetch_map(&P.tU); }
        const int ft = gp + 18 * rank;
        if (lane == 0) {
          for (int s = 0; s < 4; s++) {
            mbar_expect_tx(sb + B_FULL + 8 * s, STAGE_BYTES);
            tma2d(sb + s * STAGE_BYTES, &P.tW1, ft * 128, s * 64, sb + B_FULL + 8 * s);
            tma2d(sb + s * STAGE_BYTES + 8192, &P.tW1, ft * 128 + 64, s * 64, sb + B_FULL + 8 * s);
          }
        }
        uint32_t ready = 0;
#pragma unroll 1
        for (int kb = 0; kb < 32; kb++) {
          const uint32_t sa = sb + st * STAGE_BYTES, fb = sb + B_FULL + 8 * st;
          if (kb >= 4) {
            mbar_wait(sb + B_EMPTY + 8 * st, ph, 2);
            if (lane == 0) {
              mbar_expect_tx(fb, STAGE_BYTES);
              tma2d(sa, &P.tW1, ft * 128, kb * 64, fb);
              tma2d(sa + 8192, &P.tW1, ft * 128 + 64, kb * 64, fb);
            }
          }
          if (!((ready >> kb) & 1)) ready = poll_mask(FL_H, 32, ep1 * 32, kb, 3);
          if (lane == 0) {
#pragma unroll
            for (int i = 0; i < 3; i++) tma2d(sa + 16384 + i * 8192, &P.tH, gj * 192 + i * 64, kb * 64, fb);
          }
          __syncwarp();
          if (++st == 4) { st = 0; ph ^= 1; }
        }
        if (lane == 0) STAMP(8);
        if (gp < 16) {
          ready = 0;
#pragma unroll 1
          for (int i2 = 0; i2 < 36; i2++) {
            int tl = gp + (i2 >> 1); if (tl >= 18) tl -= 18;
            const int f0 = (18 * rank + tl) * 128 + (i2 & 1) * 64;
            const uint32_t sa = sb + st * STAGE_BYTES, fb = sb + B_FULL + 8 * st;
            mbar_wait(sb + B_EMPTY + 8 * st, ph, 4);
            if (lane == 0) {
              mbar_expect_tx(fb, i2 < 2 ? 16384 : STAGE_BYTES);
              tma2d(sa, &P.tW2, gp * 128, f0, fb);
              tma2d(sa + 8192, &P.tW2, gp * 128 + 64, f0, fb);
            }
            if (i2 >= 2) {
              if (!((ready >> tl) & 1)) ready = poll_mask(FL_U + gj * 36 + 18 * rank, 18, ep1, tl, 5);
              if (lane == 0) {
#pragma unroll
                for (int i = 0; i < 3; i++) tma2d(sa + 16384 + i * 8192, &P.tU, gj * 192 + i * 64, f0, fb);
              }
            }
            __syncwarp();
            if (++st == 4) { st = 0; ph ^= 1; }
          }
        }
      } else {
        if (lane == 0) {
          prefetch_map(&P.tXB); prefetch_map(&P.tTFk); prefetch_map(&P.tX1c); prefetch_map(&P.tZT); prefetch_map(&P.tTFn);
          wait_flag(FL_TF, ep1 * 192, 6);
#pragma unroll 1
          for (int it = 0; it < 4; it++) {
            const int item = fc + 24 * it, sblk = item & 15, nb = item >> 4;
            wait_flag(FL_XB + sblk, ep1 * 64, 7);
            fence_async_all();
#pragma unroll 1
            for (int kb = 0; kb < 5; kb++) {
              const uint32_t sa = sb + st * STAGE_BYTES, fb = sb + B_FULL + 8 * st;
              mbar_wait(sb + B_EMPTY + 8 * st, ph, 8);
              mbar_expect_tx(fb, 16384 + 12288);
              tma2d(sa, &P.tXB, (nb >= 3 ? 288 : 0) + kb * 64, sblk * 128, fb);
              tma2d(sa + 16384, &P.tTFk, kb * 64, nb * 96, fb);
              if (++st == 4) { st = 0; ph ^= 1; }
            }
          }
          STAMP(8);
          wait_flag(FL_X1, ep1 * 48, 9);
          fence_async_all();
#pragma unroll 1
          for (int b = 0; b < 2; b++)
#pragma unroll 1
            for (int w = 0; w < 2; w++) {
              const uint32_t bar = sb + B_F2 + 8 * (w * 2 + b);
              mbar_expect_tx(bar, 24576);
              for (int c = 0; c < 3; c++) {
                const int cc = w * 144 + fc * 6 + b * 3 + c;
                tma3d(sb + w * 73728 + b * 24576 + c * 8192, &P.tX1c, 0, 0, 2 * cc, bar);
              }
            }
          STAMP(9);
          wait_flag(FL_Z, ep1 * 48, 10);
          fence_async_all();
          STAMP(10);
#pragma unroll 1
          for (int it = 0; it < 2; it++) {
            const int item = fc + 24 * it, sblk = item & 15, q = item >> 4;
#pragma unroll 1
            for (int k2 = 0; k2 < 10; k2++) {
              const int krow = (k2 >= 5 ? 288 + (k2 - 5) * 64 : k2 * 64);
              const uint32_t sa = sb + st * STAGE_BYTES, fb = sb + B_FULL + 8 * st;
              mbar_wait(sb + B_EMPTY + 8 * st, ph, 11);
              mbar_expect_tx(fb, 32768);
              tma2d(sa, &P.tZT, sblk * 128, krow, fb);
              tma2d(sa + 8192, &P.tZT, sblk * 128 + 64, krow, fb);
              tma2d(sa + 16384, &P.tTFn, q * 96, krow, fb);
              tma2d(sa + 24576, &P.tTFn, q * 96 + 64, krow, fb);
              if (++st == 4) { st = 0; ph ^= 1; }
            }
          }
        }
        __syncwarp();
      }
    } else {
      if (cta < 128) {
        if (warp == 1 && lane == 0) {
          const int j0 = 64 * (cta >> 2) + 8 * (cta & 3);
          mbar_expect_tx(sb + B_W, 4 * 4624);
          bulk_ld(sb + SM_SIDE, P.Wr + (size_t)j0 * DF_, 4624, sb + B_W);
          bulk_ld(sb + SM_SIDE + 4624, P.Wr + (size_t)(j0 + 32) * DF_, 4624, sb + B_W);
          bulk_ld(sb + SM_SIDE + 9248, P.Wi + (size_t)j0 * DF_, 4624, sb + B_W);
          bulk_ld(sb + SM_SIDE + 13872, P.Wi + (size_t)(j0 + 32) * DF_, 4624, sb + B_W);
        }
        __syncwarp();
        w_job(sb, cta, tid - 32, lane);
      } else if (lane == 0) {
        mbar_arrive(sb + B_AUX);
      }
      if (lane == 0) STAMP(11 + warp);
      if (warp == 1 && isG) {
        bar_sync(1, 288);
        if (lane == 0) {
          const int ft = gp + 18 * rank;
#pragma unroll
          for (int w = 0; w < 2; w++)
#pragma unroll
            for (int i = 0; i < 3; i++) tma2d_st(&P.tU, sb + SM_STG + w * 24576 + i * 8192, gj * 192 + i * 64, ft * 128 + w * 64);
          bulk_commit();
          bulk_wait0();
          fence_async_all();
          red_release(g_flags + (FL_U + gj * 36 + ft) * 32, 1u);
          STAMP(15);
          if (gp < 16) {
            mbar_wait(sb + B_LFREE, 0, 12);
            asm volatile("barrier.cluster.wait.acquire;" ::: "memory");
            mbar_arrive_remote(mapa(sb + B_PFREE, rank ^ 1));
          }
        }
      }
    }
  } else {
    asm volatile("setmaxnreg.inc.sync.aligned.u32 224;");
    const int cw = warp - 4;
    const int wg = cw >> 2, wq = cw & 3;
    const int ct = tid - 128;
    const int q4 = lane & 3, r8 = lane >> 2;
    if (cta < 128) row_job(P, cta * 16 + cw * 2, lane);
    if (ct == 0) STAMP(0);
    uint32_t st = 0, ph = 0;
    if (isG) {
      const int ft = gp + 18 * rank;
      float bias0, bias1;
      {
        const int f = ft * 128 + wg * 64 + wq * 16 + r8;
        bias0 = __bfloat162float(P.b1[f]); bias1 = __bfloat162float(P.b1[f + 8]);
      }
      float acc[96];
      const uint64_t dA0 = mkdesc(sb + wg * 8192, 8192, 1024), dB0 = mkdesc(sb + 16384, 8192, 1024);
      uint32_t prev = 0;
#pragma unroll 1
      for (int kb = 0; kb < 32; kb++) {
        mbar_wait(sb + B_FULL + 8 * st, ph, 13);
        if (kb == 0 && ct == 0) STAMP(1);
        const uint64_t so = (uint64_t)(st * (STAGE_BYTES >> 4));
        wg_fence();
#pragma unroll
        for (int kk = 0; kk < 4; kk++) wg_ss_n192<1, 1>(acc, dA0 + so + kk * 128, dB0 + so + kk * 128, (kb | kk) != 0);
        wg_commit();
        if (kb > 0) { wg_wait<1>(); if (lane == 0) mbar_arrive(sb + B_EMPTY + 8 * prev); }
        prev = st;
        if (++st == 4) { st = 0; ph ^= 1; }
      }
      wg_wait<0>();
      if (lane == 0) mbar_arrive(sb + B_EMPTY + 8 * prev);
      if (ct == 0) STAMP(2);
      {
        const int jm = lane >> 3, i8 = lane & 7;
        const uint32_t row = wq * 16 + (jm & 1) * 8 + i8;
        const uint32_t base = sb + SM_STG + wg * 24576 + row * 128;
#pragma unroll
        for (int G = 0; G < 24; G += 2) {
          uint32_t r[4];
#pragma unroll
          for (int m = 0; m < 4; m++) {
            const float b = (m & 1) ? bias1 : bias0;
            float v0 = gelu_tanh(bfr(bfr(acc[4 * G + 2 * m]) + b)), v1 = gelu_tanh(bfr(bfr(acc[4 * G + 2 * m + 1]) + b));
            r[m] = pack2(v0, v1);
          }
          const uint32_t grp = G + (jm >> 1);
          stsm4(base + (grp >> 3) * 8192 + (((grp & 7) ^ i8) << 4), r[0], r[1], r[2], r[3]);
        }
      }
      fence_async_smem();
      bar_sync(1, 288);
      if (ct == 0) STAMP(3);
      if (gp < 16) {
        const uint64_t dS0 = mkdesc(sb + SM_STG, 8192, 1024);
#pragma unroll 1
        for (int i2 = 0; i2 < 36; i2++) {
          mbar_wait(sb + B_FULL + 8 * st, ph, 14);
          const uint64_t so = (uint64_t)(st * (STAGE_BYTES >> 4));
          const uint64_t db = i2 < 2 ? dS0 + (uint64_t)(i2 * (24576 >> 4)) : dB0 + so;
          wg_fence();
#pragma unroll
          for (int kk = 0; kk < 4; kk++) wg_ss_n192<1, 1>(acc, dA0 + so + kk * 128, db + kk * 128, (i2 | kk) != 0);
          wg_commit();
          if (i2 > 0) {
            wg_wait<1>();
            if (lane == 0) { mbar_arrive(sb + B_EMPTY + 8 * prev); if (i2 == 2) mbar_arrive(sb + B_LFREE); }
          }
          prev = st;
          if (++st == 4) { st = 0; ph ^= 1; }
        }
        wg_wait<0>();
        if (ct == 0) STAMP(4);
        asm volatile("barrier.cluster.wait.acquire;" ::: "memory");
        mbar_wait_cl(sb + B_PFREE, 0, 15);
        {
          const uint32_t rdst = mapa(sb + SM_STG + ct * 16, rank ^ 1), rbar = mapa(sb + B_X, rank ^ 1);
          if (rank == 0) {
#pragma unroll
            for (int i = 0; i < 12; i++)
              asm volatile("st.async.weak.shared::cluster.mbarrier::complete_tx::bytes.v4.f32 [%0], {%1, %2, %3, %4}, [%5];"
                           ::"r"(rdst + i * 4096), "f"(acc[48 + 4 * i]), "f"(acc[49 + 4 * i]), "f"(acc[50 + 4 * i]), "f"(acc[51 + 4 * i]), "r"(rbar) : "memory");
          } else {
#pragma unroll
            for (int i = 0; i < 12; i++)
              asm volatile("st.async.weak.shared::cluster.mbarrier::complete_tx::bytes.v4.f32 [%0], {%1, %2, %3, %4}, [%5];"
                           ::"r"(rdst + i * 4096), "f"(acc[4 * i]), "f"(acc[1 + 4 * i]), "f"(acc[2 + 4 * i]), "f"(acc[3 + 4 * i]), "r"(rbar) : "memory");
#pragma unroll
            for (int i = 0; i < 48; i++) acc[i] = acc[48 + i];
          }
        }
        const int cb = 2 * gj + rank;
        const int srow = gp * 128 + wg * 64 + wq * 16 + r8;
        if (lane == 0) { wait_flag(FL_XB + gp, ep1 * 64, 16); wait_flag(FL_A + gp * 3 + (cb % 3), ep1 * 8, 17); }
        __syncwarp();
        uint4 af[6];
#pragma unroll
        for (int i = 0; i < 6; i++) af[i] = __ldcg(g_afrag + ((size_t)(gp * 6 + cb) * 6 + i) * 256 + ct);
        const float g0 = __ldcg(g_gate + srow), g1 = __ldcg(g_gate + srow + 8);
        const float c0 = __bfloat162float(P.b2[srow]), c1 = __bfloat162float(P.b2[srow + 8]);
        const float og0 = bfr(1.0f - g0), og1 = bfr(1.0f - g1);
        bar_sync(4, 256);
        mbar_wait_cl(sb + B_X, 0, 18);
        if (ct == 0) STAMP(5);
        {
          const int jm = lane >> 3, i8 = lane & 7;
          const uint32_t row = wq * 16 + (jm & 1) * 8 + i8;
          const uint32_t obase = sb + wg * 12288 + row * 64;
#pragma unroll
          for (int i = 0; i < 6; i++) {
            float v[8];
#pragma unroll
            for (int hh = 0; hh < 2; hh++) {
              float4 pz;
              asm volatile("ld.shared.v4.f32 {%0, %1, %2, %3}, [%4];" : "=f"(pz.x), "=f"(pz.y), "=f"(pz.z), "=f"(pz.w) : "r"(sb + SM_STG + ct * 16 + (2 * i + hh) * 4096));
              v[4 * hh] = acc[8 * i + 4 * hh] + pz.x; v[4 * hh + 1] = acc[8 * i + 4 * hh + 1] + pz.y;
              v[4 * hh + 2] = acc[8 * i + 4 * hh + 2] + pz.z; v[4 * hh + 3] = acc[8 * i + 4 * hh + 3] + pz.w;
            }
            const uint32_t aw[4] = {af[i].x, af[i].y, af[i].z, af[i].w};
            uint32_t r[4];
#pragma unroll
            for (int m = 0; m < 4; m++) {
              const float g = (m & 1) ? g1 : g0, og = (m & 1) ? og1 : og0, c = (m & 1) ? c1 : c0;
              float b0 = bfr(bfr(v[2 * m]) + c), b1 = bfr(bfr(v[2 * m + 1]) + c);
              float o0 = bfr(g * bf_lo(aw[m])) + bfr(og * b0), o1 = bfr(g * bf_hi(aw[m])) + bfr(og * b1);
              r[m] = pack2(o0, o1);
            }
            const uint32_t grp = 2 * i + (jm >> 1);
            stsm4(obase + (grp >> 2) * 4096 + (((grp & 3) ^ ((row >> 1) & 3)) << 4), r[0], r[1], r[2], r[3]);
          }
        }
        fence_async_smem();
        bar_sync(2 + wg, 128);
        if ((ct & 127) == 0) {
#pragma unroll
          for (int i = 0; i < 3; i++) tma2d_st(&P.tOut, sb + wg * 12288 + i * 4096, cb * 96 + i * 32, gp * 128 + wg * 64);
          bulk_commit();
          bulk_wait0_read();
        }
        if (ct == 0) STAMP(6);
      }
    } else {
      tf_gen(fc * 256 + ct, lane);
      if (fc == 0 && wg == 0) {
#pragma unroll 2
        for (int t = 0; t < 16; t++) {
          const int j = ct + 128 * t, jn = (S_ - j) & (S_ - 1);
          const float ar = __bfloat162float(P.Wr[j * DF_]), ai = __bfloat162float(P.Wi[j * DF_]);
          const float br = __bfloat162float(P.Wr[jn * DF_]), bi = __bfloat162float(P.Wi[jn * DF_]);
          const float cr = __bfloat162float(P.Wr[j * DF_ + 288]), ci = __bfloat162float(P.Wi[j * DF_ + 288]);
          const float dr = __bfloat162float(P.Wr[jn * DF_ + 288]), di = __bfloat162float(P.Wi[jn * DF_ + 288]);
          const float h0r = 0.5f * (ar + br), h0i = 0.5f * (ai - bi), h1r = 0.5f * (cr + dr), h1i = 0.5f * (ci - di);
          g_UV[j] = make_float4(0.25f * (h0r + h1r), 0.25f * (h0i + h1i), 0.25f * (h0r - h1r), 0.25f * (h0i - h1i));
        }
      }
      if (ct == 0) STAMP(1);
      {
        const uint64_t dA0 = mkdesc(sb + wg * 8192, 16, 1024), dB0 = mkdesc(sb + 16384, 16, 1024);
        float acc[48];
        uint32_t prev = 0;
#pragma unroll 1
        for (int it = 0; it < 4; it++) {
          const int item = fc + 24 * it, sblk = item & 15, nb = item >> 4;
#pragma unroll
          for (int kb = 0; kb < 5; kb++) {
            mbar_wait(sb + B_FULL + 8 * st, ph, 19);
            const uint64_t so = (uint64_t)(st * (STAGE_BYTES >> 4));
            wg_fence();
#pragma unroll
            for (int kk = 0; kk < (kb < 4 ? 4 : 2); kk++) wg_ss_n96<0, 0>(acc, dA0 + so + kk * 2, dB0 + so + kk * 2, (kb | kk) != 0);
            wg_commit();
            if (kb > 0) { wg_wait<1>(); if (lane == 0) mbar_arrive(sb + B_EMPTY + 8 * prev); }
            prev = st;
            if (++st == 4) { st = 0; ph ^= 1; }
          }
          wg_wait<0>();
          if (lane == 0) mbar_arrive(sb + B_EMPTY + 8 * prev);
          if ((ct & 127) == 0) bulk_wait0_read();
          bar_sync(2 + wg, 128);
          const int jm = lane >> 3, i8 = lane & 7;
          const uint32_t base = sb + SM_STG + wg * 12288;
#pragma unroll
          for (int G = 0; G < 12; G += 2) {
            const uint32_t row = 8 * (G + (jm >> 1)) + i8;
            stsm4t(base + row * 128 + (((2 * wq + (jm & 1)) ^ i8) << 4), pack2(acc[4 * G], acc[4 * G + 1]), pack2(acc[4 * G + 2], acc[4 * G + 3]),
                   pack2(acc[4 * G + 4], acc[4 * G + 5]), pack2(acc[4 * G + 6], acc[4 * G + 7]));
          }
          fence_async_smem();
          bar_sync(2 + wg, 128);
          if ((ct & 127) == 0) { tma2d_st(&P.tX1s, base, sblk * 128 + wg * 64, nb * 96); bulk_commit(); }
        }
        if ((ct & 127) == 0) { bulk_wait0(); fence_async_all(); red_release(g_flags + FL_X1 * 32, 1u); }
      }
      if (ct == 0) STAMP(2);
      {
        mbar_wait(sb + B_AUX, 0, 20);
#pragma unroll 1
        for (int idx = ct; idx < 128 * 32; idx += 256) {
          const int n = idx >> 5, k = (idx & 31) * 2;
          const int g = n >> 3, qq = (n >> 1) & 3, cs = n & 1;
          const int pi = 16 * (g >> 2) + 8 * ((g >> 1) & 1) + 2 * qq + (g & 1);
          const float a0 = (float)((k * pi) & 63) * (1.0f / 32.0f), a1 = (float)(((k + 1) * pi) & 63) * (1.0f / 32.0f);
          const float v0 = cs ? sinpif(a0) : cospif(a0), v1 = cs ? sinpif(a1) : cospif(a1);
          const uint32_t addr = sb + SM_SIDE + n * 128 + (((k >> 3) ^ (n & 7)) << 4) + (k & 7) * 2;
          asm volatile("st.shared.u32 [%0], %1;" ::"r"(addr), "r"(pack2(v0, v1)) : "memory");
        }
        const int j1 = 8 * wq + r8;
        const uint32_t atab = sb + SM_STG + 24576 + (ct & 127) * 16;
#pragma unroll 1
        for (int t = 0; t < 4; t++) {
          uint32_t av[4];
#pragma unroll
          for (int m = 0; m < 4; m++) {
            const int k0 = 16 * t + 8 * (m >> 1) + 2 * q4;
            float v[2];
#pragma unroll
            for (int e = 0; e < 2; e++) {
              const int k = k0 + e;
              if (wg == 0) {
                const float an = (float)((j1 * (k & 31)) & 31) * (1.0f / 16.0f);
                const float c = cospif(an), s = sinpif(an);
                v[e] = ((m & 1) == (k >> 5)) ? c : ((m & 1) ? -s : s);
              } else {
                const int row = 16 * wq + 8 * (m & 1) + r8;
                const int rip = row >> 5, s1 = row & 31, ri = (k >> 3) & 1, jj = 8 * (k >> 4) + (k & 7);
                const float an = (float)((s1 * jj) & 31) * (1.0f / 16.0f);
                const float c = cospif(an), s = sinpif(an);
                v[e] = (rip == ri) ? c : (rip ? s : -s);
              }
            }
            av[m] = pack2(v[0], v[1]);
          }
          asm volatile("st.shared.v4.b32 [%0], {%1, %2, %3, %4};" ::"r"(atab + wg * 8192 + t * 2048), "r"(av[0]), "r"(av[1]), "r"(av[2]), "r"(av[3]) : "memory");
        }
        float twc[16], tws[16];
#pragma unroll
        for (int G = 0; G < 8; G++)
#pragma unroll
          for (int e = 0; e < 2; e++) {
            const float an = (float)(j1 * (8 * G + 2 * q4 + e)) * (1.0f / 1024.0f);
            twc[2 * G + e] = cospif(an); tws[2 * G + e] = sinpif(an);
          }
        fence_async_smem();
        if (lane == 0) wait_flag(FL_WT, ep1 * 384, 21);
        bar_sync(4, 256);
        const uint64_t dC = mkdesc(sb + SM_SIDE, 16, 1024);
        const uint32_t wbase = sb + wg * 73728;
        const int jm = lane >> 3, i8 = lane & 7;
        const uint32_t strow = (16 * wq + 8 * (jm & 1) + i8) * 128;
        constexpr float SCALE = 2.0f / (2048.0f * 576.0f);
#pragma unroll 1
        for (int b = 0; b < 2; b++) {
          const uint32_t xbuf = wbase + b * 24576, tbuf = wbase + 49152;
          uint32_t Yp[3][16];
          {
            float acc[96];
            mbar_wait(sb + B_F2 + 8 * (wg * 2 + b), 0, 22);
            const uint64_t dX = mkdesc(xbuf, 8192, 1024);
            uint32_t Af[16];
#pragma unroll
            for (int t = 0; t < 4; t++)
              asm volatile("ld.shared.v4.b32 {%0, %1, %2, %3}, [%4];" : "=r"(Af[4 * t]), "=r"(Af[4 * t + 1]), "=r"(Af[4 * t + 2]), "=r"(Af[4 * t + 3]) : "r"(atab + t * 2048));
            wg_fence();
#pragma unroll
            for (int t = 0; t < 4; t++) wg_rs_n192<1>(acc, Af[4 * t], Af[4 * t + 1], Af[4 * t + 2], Af[4 * t + 3], dX + t * 128, t != 0);
            wg_commit();
            wg_wait<0>();
#pragma unroll
            for (int c = 0; c < 3; c++)
#pragma unroll
              for (int G = 0; G < 8; G++) {
                const float* a = &acc[32 * c + 4 * G];
                const float c0 = twc[2 * G], s0 = tws[2 * G], c1 = twc[2 * G + 1], s1 = tws[2 * G + 1];
                Yp[c][4 * (G >> 1) + 2 * (G & 1)] = pack2(a[0] * c0 + a[2] * s0, a[1] * c1 + a[3] * s1);
                Yp[c][4 * (G >> 1) + 2 * (G & 1) + 1] = pack2(a[2] * c0 - a[0] * s0, a[3] * c1 - a[1] * s1);
              }
          }
#pragma unroll
          for (int c = 0; c < 3; c++) {
            const int cc = wg * 144 + fc * 6 + b * 3 + c;
            uint2 Wv[8];
            {
              const uint2* wp = reinterpret_cast<const uint2*>(g_Wt + (size_t)cc * 2048) + q4 * 32 + j1;
#pragma unroll
              for (int G = 0; G < 8; G++) Wv[G] = __ldcg(wp + G * 128);
            }
            float acc[64];
            wg_fence();
#pragma unroll
            for (int t = 0; t < 4; t++) wg_rs_n128<0>(acc, Yp[c][4 * t], Yp[c][4 * t + 1], Yp[c][4 * t + 2], Yp[c][4 * t + 3], dC + t * 2, t != 0);
            wg_commit();
            wg_wait<0>();
            uint32_t Pp[16];
            if (c == 0 && b == 0 && cc == 0) {
              const uint32_t scr = sb + 147456;
#pragma unroll
              for (int g = 0; g < 16; g++) {
                const int j = j1 + 32 * (8 * (g >> 1) + 2 * q4 + (g & 1));
                asm volatile("st.shared.v2.f32 [%0], {%1, %2};" ::"r"(scr + j * 8), "f"(acc[4 * g] + acc[4 * g + 3]), "f"(acc[4 * g + 2] - acc[4 * g + 1]) : "memory");
              }
              bar_sync(2 + wg, 128);
#pragma unroll
              for (int G = 0; G < 8; G++) {
                float pr[2], pi[2];
#pragma unroll
                for (int e = 0; e < 2; e++) {
                  const int g = 2 * G + e;
                  const int j = j1 + 32 * (8 * G + 2 * q4 + e), jn = (S_ - j) & (S_ - 1);
                  float nr, ni;
                  asm volatile("ld.shared.v2.f32 {%0, %1}, [%2];" : "=f"(nr), "=f"(ni) : "r"(scr + jn * 8));
                  const float4 uv = g_UV[j];
                  const float xr = acc[4 * g] + acc[4 * g + 3], xi = acc[4 * g + 2] - acc[4 * g + 1];
                  pr[e] = uv.x * xr - uv.y * xi + uv.z * nr + uv.w * ni;
                  pi[e] = uv.x * xi + uv.y * xr + uv.w * nr - uv.z * ni;
                }
                Pp[4 * (G >> 1) + 2 * (G & 1)] = pack2(pr[0], pr[1]);
                Pp[4 * (G >> 1) + 2 * (G & 1) + 1] = pack2(pi[0], pi[1]);
              }
            } else {
#pragma unroll
              for (int G = 0; G < 8; G++) {
                const float* a = &acc[8 * G];
                const float x0r = a[0] + a[3], x0i = a[2] - a[1], x1r = a[4] + a[7], x1i = a[6] - a[5];
                const float w0r = bf_lo(Wv[G].x), w0i = bf_hi(Wv[G].x), w1r = bf_lo(Wv[G].y), w1i = bf_hi(Wv[G].y);
                Pp[4 * (G >> 1) + 2 * (G & 1)] = pack2(x0r * w0r - x0i * w0i, x1r * w1r - x1i * w1i);
                Pp[4 * (G >> 1) + 2 * (G & 1) + 1] = pack2(x0r * w0i + x0i * w0r, x1r * w1i + x1i * w1r);
              }
            }
            wg_fence();
#pragma unroll
            for (int t = 0; t < 4; t++) wg_rs_n128<0>(acc, Pp[4 * t], Pp[4 * t + 1], Pp[4 * t + 2], Pp[4 * t + 3], dC + t * 2, t != 0);
            wg_commit();
            wg_wait<0>();
#pragma unroll
            for (int G = 0; G < 8; G += 2) {
              uint32_t r[4];
#pragma unroll
              for (int h = 0; h < 2; h++) {
                const float* a = &acc[8 * (G + h)];
                const float v0r = a[0] - a[3], v0i = a[2] + a[1], v1r = a[4] - a[7], v1i = a[6] + a[5];
                const float c0 = twc[2 * (G + h)] * SCALE, s0 = tws[2 * (G + h)] * SCALE, c1 = twc[2 * (G + h) + 1] * SCALE, s1 = tws[2 * (G + h) + 1] * SCALE;
                r[2 * h] = pack2(v0r * c0 - v0i * s0, v1r * c1 - v1i * s1);
                r[2 * h + 1] = pack2(v0i * c0 + v0r * s0, v1i * c1 + v1r * s1);
              }
              stsm4(tbuf + c * 8192 + strow + (((G + (jm >> 1)) ^ i8) << 4), r[0], r[1], r[2], r[3]);
            }
          }
          fence_async_smem();
          bar_sync(2 + wg, 128);
          {
            float acc[96];
            const uint64_t dT = mkdesc(tbuf, 8192, 1024);
            uint32_t Ai[16];
#pragma unroll
            for (int t = 0; t < 4; t++)
              asm volatile("ld.shared.v4.b32 {%0, %1, %2, %3}, [%4];" : "=r"(Ai[4 * t]), "=r"(Ai[4 * t + 1]), "=r"(Ai[4 * t + 2]), "=r"(Ai[4 * t + 3]) : "r"(atab + 8192 + t * 2048));
            wg_fence();
#pragma unroll
            for (int t = 0; t < 4; t++) wg_rs_n192<1>(acc, Ai[4 * t], Ai[4 * t + 1], Ai[4 * t + 2], Ai[4 * t + 3], dT + t * 128, t != 0);
            wg_commit();
            wg_wait<0>();
#pragma unroll
            for (int c = 0; c < 3; c++)
#pragma unroll
              for (int G = 0; G < 8; G += 2) {
                const float* a = &acc[32 * c + 4 * G];
                stsm4(xbuf + c * 8192 + strow + (((G + (jm >> 1)) ^ i8) << 4), pack2(a[0], a[1]), pack2(a[2], a[3]), pack2(a[4], a[5]), pack2(a[6], a[7]));
              }
          }
          fence_async_smem();
          bar_sync(2 + wg, 128);
          if ((ct & 127) == 0) {
#pragma unroll
            for (int c = 0; c < 3; c++) tma3d_st(&P.tZc, xbuf + c * 8192, 0, 0, 2 * (wg * 144 + fc * 6 + b * 3 + c));
            bulk_commit();
          }
        }
        if ((ct & 127) == 0) { bulk_wait0(); fence_async_all(); red_release(g_flags + FL_Z * 32, 1u); }
      }
      if (ct == 0) STAMP(3);
      {
        const uint64_t dA0 = mkdesc(sb + wg * 8192, 8192, 1024), dB0 = mkdesc(sb + 16384, 8192, 1024);
        uint32_t prev = 0;
#pragma unroll 1
        for (int it = 0; it < 2; it++) {
          const int item = fc + 24 * it, sblk = item & 15, q = item >> 4;
          float ev[48], od[48];
#pragma unroll
          for (int k2 = 0; k2 < 10; k2++) {
            mbar_wait(sb + B_FULL + 8 * st, ph, 23);
            const uint64_t so = (uint64_t)(st * (STAGE_BYTES >> 4));
            wg_fence();
#pragma unroll
            for (int kk = 0; kk < ((k2 % 5) < 4 ? 4 : 2); kk++) {
              if (k2 < 5) wg_ss_n96<1, 1>(ev, dA0 + so + kk * 128, dB0 + so + kk * 128, (k2 | kk) != 0);
              else wg_ss_n96<1, 1>(od, dA0 + so + kk * 128, dB0 + so + kk * 128, ((k2 - 5) | kk) != 0);
            }
            wg_commit();
            if (k2 > 0) { wg_wait<1>(); if (lane == 0) mbar_arrive(sb + B_EMPTY + 8 * prev); }
            prev = st;
            if (++st == 4) { st = 0; ph ^= 1; }
          }
          wg_wait<0>();
          if (lane == 0) mbar_arrive(sb + B_EMPTY + 8 * prev);
#pragma unroll
          for (int i = 0; i < 6; i++) {
            uint4 p, m;
            p.x = pack2(ev[8 * i] + od[8 * i], ev[8 * i + 1] + od[8 * i + 1]); m.x = pack2(ev[8 * i] - od[8 * i], ev[8 * i + 1] - od[8 * i + 1]);
            p.y = pack2(ev[8 * i + 2] + od[8 * i + 2], ev[8 * i + 3] + od[8 * i + 3]); m.y = pack2(ev[8 * i + 2] - od[8 * i + 2], ev[8 * i + 3] - od[8 * i + 3]);
            p.z = pack2(ev[8 * i + 4] + od[8 * i + 4], ev[8 * i + 5] + od[8 * i + 5]); m.z = pack2(ev[8 * i + 4] - od[8 * i + 4], ev[8 * i + 5] - od[8 * i + 5]);
            p.w = pack2(ev[8 * i + 6] + od[8 * i + 6], ev[8 * i + 7] + od[8 * i + 7]); m.w = pack2(ev[8 * i + 6] - od[8 * i + 6], ev[8 * i + 7] - od[8 * i + 7]);
            g_afrag[((size_t)(sblk * 6 + q) * 6 + i) * 256 + ct] = p;
            g_afrag[((size_t)(sblk * 6 + q + 3) * 6 + i) * 256 + ct] = m;
          }
          __syncwarp();
          if (lane == 0) red_release(g_flags + (FL_A + sblk * 3 + q) * 32, 1u);
        }
      }
      if (ct == 0) STAMP(4);
    }
  }
}

typedef CUresult (*EncFn)(CUtensorMap*, CUtensorMapDataType, cuuint32_t, void*, const cuuint64_t*, const cuuint64_t*, const cuuint32_t*,
                          const cuuint32_t*, CUtensorMapInterleave, CUtensorMapSwizzle, CUtensorMapL2promotion, CUtensorMapFloatOOBfill);

void mk2d(EncFn enc, CUtensorMap* m, const void* p, uint64_t inner, uint64_t outer, uint32_t bi, uint32_t bo, CUtensorMapSwizzle sw) {
  cuuint64_t dims[2] = {inner, outer}; cuuint64_t str[1] = {inner * 2}; cuuint32_t box[2] = {bi, bo}; cuuint32_t es[2] = {1, 1};
  enc(m, CU_TENSOR_MAP_DATA_TYPE_BFLOAT16, 2, const_cast<void*>(p), dims, str, box, es, CU_TENSOR_MAP_INTERLEAVE_NONE, sw,
      CU_TENSOR_MAP_L2_PROMOTION_L2_256B, CU_TENSOR_MAP_FLOAT_OOB_FILL_NONE);
}
void mk3d(EncFn enc, CUtensorMap* m, const void* p) {
  cuuint64_t dims[3] = {64, 32, 576}; cuuint64_t str[2] = {128, 4096}; cuuint32_t box[3] = {64, 32, 2}; cuuint32_t es[3] = {1, 1, 1};
  enc(m, CU_TENSOR_MAP_DATA_TYPE_BFLOAT16, 3, const_cast<void*>(p), dims, str, box, es, CU_TENSOR_MAP_INTERLEAVE_NONE, CU_TENSOR_MAP_SWIZZLE_128B,
      CU_TENSOR_MAP_L2_PROMOTION_L2_256B, CU_TENSOR_MAP_FLOAT_OOB_FILL_NONE);
}

}

extern "C" void kernel_launch(void* const* d_in, const int* in_sizes, int n_in, void* d_out, int out_size) {
  (void)in_sizes; (void)n_in; (void)out_size;
  static EncFn enc = nullptr;
  static void *p_h, *p_u, *p_xb, *p_TF, *p_X1T, *p_ZT;
  if (!enc) {
    void* fn = nullptr;
    cudaDriverEntryPointQueryResult qr;
    cudaGetDriverEntryPoint("cuTensorMapEncodeTiled", &fn, cudaEnableDefault, &qr);
    enc = (EncFn)fn;
    cudaFuncSetAttribute(mega_kernel, cudaFuncAttributeMaxDynamicSharedMemorySize, SM_TOTAL);
    cudaGetSymbolAddress(&p_h, g_h); cudaGetSymbolAddress(&p_u, g_u); cudaGetSymbolAddress(&p_xb, g_xb);
    cudaGetSymbolAddress(&p_TF, g_TF); cudaGetSymbolAddress(&p_X1T, g_X1T); cudaGetSymbolAddress(&p_ZT, g_ZT);
  }
  Params P;
  const CUtensorMapSwizzle S128 = CU_TENSOR_MAP_SWIZZLE_128B;
  mk2d(enc, &P.tW1, d_in[4], F_, S_, 64, 64, S128);
  mk2d(enc, &P.tH, p_h, D_, S_, 64, 64, S128);
  mk2d(enc, &P.tW2, d_in[6], S_, F_, 64, 64, S128);
  mk2d(enc, &P.tU, p_u, D_, F_, 64, 64, S128);
  mk2d(enc, &P.tOut, d_out, D_, S_, 32, 64, CU_TENSOR_MAP_SWIZZLE_64B);
  mk2d(enc, &P.tXB, p_xb, D_, S_, 64, 128, S128);
  mk2d(enc, &P.tTFk, p_TF, 288, 576, 64, 96, S128);
  mk2d(enc, &P.tX1s, p_X1T, S_, 576, 64, 96, S128);
  mk3d(enc, &P.tX1c, p_X1T);
  mk3d(enc, &P.tZc, p_ZT);
  mk2d(enc, &P.tZT, p_ZT, S_, 576, 64, 64, S128);
  mk2d(enc, &P.tTFn, p_TF, 288, 576, 64, 64, S128);
  P.Ax = (const bf16*)d_in[0]; P.Wr = (const bf16*)d_in[1]; P.Wi = (const bf16*)d_in[2];
  P.b1 = (const bf16*)d_in[5]; P.b2 = (const bf16*)d_in[7]; P.gw = (const bf16*)d_in[8];

  cudaLaunchConfig_t cfg = {};
  cfg.gridDim = dim3(NCTA); cfg.blockDim = dim3(NTHREADS); cfg.dynamicSmemBytes = SM_TOTAL; cfg.stream = cudaStreamPerThread;
  cudaLaunchAttribute at[1];
  at[0].id = cudaLaunchAttributeClusterDimension; at[0].val.clusterDim.x = 2; at[0].val.clusterDim.y = 1; at[0].val.clusterDim.z = 1;
  cfg.attrs = at; cfg.numAttrs = 1;
  cudaLaunchKernelEx(&cfg, mega_kernel, P);
}
```

```cpp
#include <cuda_runtime.h>
#include <cuda_bf16.h>
#include <cuda.h>
#include <stdint.h>

template<int TA, int TB> __device__ __forceinline__ void wg_ss_n192(float (&d)[96], uint64_t da, uint64_t db, int sd) {
  asm volatile("{\n.reg .pred p;\nsetp.ne.b32 p, %98, 0;\n"
    "wgmma.mma_async.sync.aligned.m64n192k16.f32.bf16.bf16 {%0, %1, %2, %3, %4, %5, %6, %7, %8, %9, %10, %11, %12, %13, %14, %15, %16, %17, %18, %19, %20, %21, %22, %23, %24, %25, %26, %27, %28, %29, %30, %31, %32, %33, %34, %35, %36, %37, %38, %39, %40, %41, %42, %43, %44, %45, %46, %47, %48, %49, %50, %51, %52, %53, %54, %55, %56, %57, %58, %59, %60, %61, %62, %63, %64, %65, %66, %67, %68, %69, %70, %71, %72, %73, %74, %75, %76, %77, %78, %79, %80, %81, %82, %83, %84, %85, %86, %87, %88, %89, %90, %91, %92, %93, %94, %95}, %96, %97, p, 1, 1, %99, %100;\n}\n"
    : "+f"(d[0]), "+f"(d[1]), "+f"(d[2]), "+f"(d[3]), "+f"(d[4]), "+f"(d[5]), "+f"(d[6]), "+f"(d[7]), "+f"(d[8]), "+f"(d[9]), "+f"(d[10]), "+f"(d[11]), "+f"(d[12]), "+f"(d[13]), "+f"(d[14]), "+f"(d[15]), "+f"(d[16]), "+f"(d[17]), "+f"(d[18]), "+f"(d[19]), "+f"(d[20]), "+f"(d[21]), "+f"(d[22]), "+f"(d[23]), "+f"(d[24]), "+f"(d[25]), "+f"(d[26]), "+f"(d[27]), "+f"(d[28]), "+f"(d[29]), "+f"(d[30]), "+f"(d[31]), "+f"(d[32]), "+f"(d[33]), "+f"(d[34]), "+f"(d[35]), "+f"(d[36]), "+f"(d[37]), "+f"(d[38]), "+f"(d[39]), "+f"(d[40]), "+f"(d[41]), "+f"(d[42]), "+f"(d[43]), "+f"(d[44]), "+f"(d[45]), "+f"(d[46]), "+f"(d[47]), "+f"(d[48]), "+f"(d[49]), "+f"(d[50]), "+f"(d[51]), "+f"(d[52]), "+f"(d[53]), "+f"(d[54]), "+f"(d[55]), "+f"(d[56]), "+f"(d[57]), "+f"(d[58]), "+f"(d[59]), "+f"(d[60]), "+f"(d[61]), "+f"(d[62]), "+f"(d[63]), "+f"(d[64]), "+f"(d[65]), "+f"(d[66]), "+f"(d[67]), "+f"(d[68]), "+f"(d[69]), "+f"(d[70]), "+f"(d[71]), "+f"(d[72]), "+f"(d[73]), "+f"(d[74]), "+f"(d[75]), "+f"(d[76]), "+f"(d[77]), "+f"(d[78]), "+f"(d[79]), "+f"(d[80]), "+f"(d[81]), "+f"(d[82]), "+f"(d[83]), "+f"(d[84]), "+f"(d[85]), "+f"(d[86]), "+f"(d[87]), "+f"(d[88]), "+f"(d[89]), "+f"(d[90]), "+f"(d[91]), "+f"(d[92]), "+f"(d[93]), "+f"(d[94]), "+f"(d[95])
    : "l"(da), "l"(db), "r"(sd), "n"(TA), "n"(TB));
}

template<int TA, int TB> __device__ __forceinline__ void wg_ss_n96(float (&d)[48], uint64_t da, uint64_t db, int sd) {
  asm volatile("{\n.reg .pred p;\nsetp.ne.b32 p, %50, 0;\n"
    "wgmma.mma_async.sync.aligned.m64n96k16.f32.bf16.bf16 {%0, %1, %2, %3, %4, %5, %6, %7, %8, %9, %10, %11, %12, %13, %14, %15, %16, %17, %18, %19, %20, %21, %22, %23, %24, %25, %26, %27, %28, %29, %30, %31, %32, %33, %34, %35, %36, %37, %38, %39, %40, %41, %42, %43, %44, %45, %46, %47}, %48, %49, p, 1, 1, %51, %52;\n}\n"
    : "+f"(d[0]), "+f"(d[1]), "+f"(d[2]), "+f"(d[3]), "+f"(d[4]), "+f"(d[5]), "+f"(d[6]), "+f"(d[7]), "+f"(d[8]), "+f"(d[9]), "+f"(d[10]), "+f"(d[11]), "+f"(d[12]), "+f"(d[13]), "+f"(d[14]), "+f"(d[15]), "+f"(d[16]), "+f"(d[17]), "+f"(d[18]), "+f"(d[19]), "+f"(d[20]), "+f"(d[21]), "+f"(d[22]), "+f"(d[23]), "+f"(d[24]), "+f"(d[25]), "+f"(d[26]), "+f"(d[27]), "+f"(d[28]), "+f"(d[29]), "+f"(d[30]), "+f"(d[31]), "+f"(d[32]), "+f"(d[33]), "+f"(d[34]), "+f"(d[35]), "+f"(d[36]), "+f"(d[37]), "+f"(d[38]), "+f"(d[39]), "+f"(d[40]), "+f"(d[41]), "+f"(d[42]), "+f"(d[43]), "+f"(d[44]), "+f"(d[45]), "+f"(d[46]), "+f"(d[47])
    : "l"(da), "l"(db), "r"(sd), "n"(TA), "n"(TB));
}

template<int TB> __device__ __forceinline__ void wg_rs_n64(float (&d)[32], uint32_t a0, uint32_t a1, uint32_t a2, uint32_t a3, uint64_t db, int sd) {
  asm volatile("{\n.reg .pred p;\nsetp.ne.b32 p, %37, 0;\n"
    "wgmma.mma_async.sync.aligned.m64n64k16.f32.bf16.bf16 {%0, %1, %2, %3, %4, %5, %6, %7, %8, %9, %10, %11, %12, %13, %14, %15, %16, %17, %18, %19, %20, %21, %22, %23, %24, %25, %26, %27, %28, %29, %30, %31}, {%32, %33, %34, %35}, %36, p, 1, 1, %38;\n}\n"
    : "+f"(d[0]), "+f"(d[1]), "+f"(d[2]), "+f"(d[3]), "+f"(d[4]), "+f"(d[5]), "+f"(d[6]), "+f"(d[7]), "+f"(d[8]), "+f"(d[9]), "+f"(d[10]), "+f"(d[11]), "+f"(d[12]), "+f"(d[13]), "+f"(d[14]), "+f"(d[15]), "+f"(d[16]), "+f"(d[17]), "+f"(d[18]), "+f"(d[19]), "+f"(d[20]), "+f"(d[21]), "+f"(d[22]), "+f"(d[23]), "+f"(d[24]), "+f"(d[25]), "+f"(d[26]), "+f"(d[27]), "+f"(d[28]), "+f"(d[29]), "+f"(d[30]), "+f"(d[31])
    : "r"(a0), "r"(a1), "r"(a2), "r"(a3), "l"(db), "r"(sd), "n"(TB));
}

template<int TB> __device__ __forceinline__ void wg_rs_n128(float (&d)[64], uint32_t a0, uint32_t a1, uint32_t a2, uint32_t a3, uint64_t db, int sd) {
  asm volatile("{\n.reg .pred p;\nsetp.ne.b32 p, %69, 0;\n"
    "wgmma.mma_async.sync.aligned.m64n128k16.f32.bf16.bf16 {%0, %1, %2, %3, %4, %5, %6, %7, %8, %9, %10, %11, %12, %13, %14, %15, %16, %17, %18, %19, %20, %21, %22, %23, %24, %25, %26, %27, %28, %29, %30, %31, %32, %33, %34, %35, %36, %37, %38, %39, %40, %41, %42, %43, %44, %45, %46, %47, %48, %49, %50, %51, %52, %53, %54, %55, %56, %57, %58, %59, %60, %61, %62, %63}, {%64, %65, %66, %67}, %68, p, 1, 1, %70;\n}\n"
    : "+f"(d[0]), "+f"(d[1]), "+f"(d[2]), "+f"(d[3]), "+f"(d[4]), "+f"(d[5]), "+f"(d[6]), "+f"(d[7]), "+f"(d[8]), "+f"(d[9]), "+f"(d[10]), "+f"(d[11]), "+f"(d[12]), "+f"(d[13]), "+f"(d[14]), "+f"(d[15]), "+f"(d[16]), "+f"(d[17]), "+f"(d[18]), "+f"(d[19]), "+f"(d[20]), "+f"(d[21]), "+f"(d[22]), "+f"(d[23]), "+f"(d[24]), "+f"(d[25]), "+f"(d[26]), "+f"(d[27]), "+f"(d[28]), "+f"(d[29]), "+f"(d[30]), "+f"(d[31]), "+f"(d[32]), "+f"(d[33]), "+f"(d[34]), "+f"(d[35]), "+f"(d[36]), "+f"(d[37]), "+f"(d[38]), "+f"(d[39]), "+f"(d[40]), "+f"(d[41]), "+f"(d[42]), "+f"(d[43]), "+f"(d[44]), "+f"(d[45]), "+f"(d[46]), "+f"(d[47]), "+f"(d[48]), "+f"(d[49]), "+f"(d[50]), "+f"(d[51]), "+f"(d[52]), "+f"(d[53]), "+f"(d[54]), "+f"(d[55]), "+f"(d[56]), "+f"(d[57]), "+f"(d[58]), "+f"(d[59]), "+f"(d[60]), "+f"(d[61]), "+f"(d[62]), "+f"(d[63])
    : "r"(a0), "r"(a1), "r"(a2), "r"(a3), "l"(db), "r"(sd), "n"(TB));
}

namespace {

typedef __nv_bfloat16 bf16;

constexpr int S_ = 2048, D_ = 576, F_ = 4608, DF_ = 289;
constexpr int NCTA = 132, NG = 108, NTHREADS = 384;

constexpr uint32_t STAGE_BYTES = 40960;
constexpr uint32_t SM_STG = 163840;
constexpr uint32_t SM_SIDE = 212992;
constexpr uint32_t SM_BAR = 231680;
constexpr uint32_t SM_TOTAL = 232448;
constexpr uint32_t B_FULL = SM_BAR, B_EMPTY = SM_BAR + 32, B_X = SM_BAR + 64, B_PFREE = SM_BAR + 72, B_LFREE = SM_BAR + 80,
                   B_W = SM_BAR + 88, B_AUX = SM_BAR + 96, B_F2 = SM_BAR + 104  , SM_EPOCH = SM_BAR + 144;

constexpr int FL_H = 0, FL_U = 32, FL_XB = 140, FL_TF = 156, FL_WT = 157, FL_X1 = 158, FL_Z = 159, FL_A = 160, NFLAGS = 208;

struct Params {
  CUtensorMap tW1, tH, tW2, tU, tOut, tXB, tTFk, tX1s, tX1c, tZc, tZT, tTFn;
  const bf16 *Ax, *Wr, *Wi, *b1, *b2, *gw;
};

}

__device__ __align__(1024) bf16 g_h[S_ * D_];
__device__ __align__(1024) bf16 g_u[F_ * D_];
__device__ __align__(1024) bf16 g_xb[S_ * D_];
__device__ __align__(1024) bf16 g_TF[576 * 288];
__device__ __align__(1024) bf16 g_X1T[576 * S_];
__device__ __align__(1024) bf16 g_ZT[576 * S_];
__device__ __align__(1024) uint32_t g_Wt[288 * 2048];
__device__ __align__(1024) uint4 g_afrag[16 * 6 * 6 * 256];
__device__ __align__(1024) uint2 g_W0[2048];
__device__ __align__(1024) float g_gate[S_];
__device__ __align__(1024) unsigned g_flags[NFLAGS * 32];
__device__ __align__(1024) unsigned g_epoch[NCTA * 32];

#define STAMP(i) do { } while (0)

namespace {

constexpr long long TIMEOUT_CYC = 400000000LL;

__device__ __forceinline__ bool on_timeout(int site) {
  __trap();
  return true;
}
__device__ __forceinline__ bool aborted() {
  return false;
}

__device__ __forceinline__ uint32_t smem_u32(const void* p) { return (uint32_t)__cvta_generic_to_shared(p); }
__device__ __forceinline__ void mbar_init(uint32_t bar, uint32_t cnt) { asm volatile("mbarrier.init.shared::cta.b64 [%0], %1;" ::"r"(bar), "r"(cnt) : "memory"); }
__device__ __forceinline__ void mbar_expect_tx(uint32_t bar, uint32_t bytes) { asm volatile("mbarrier.arrive.expect_tx.shared::cta.b64 _, [%0], %1;" ::"r"(bar), "r"(bytes) : "memory"); }
__device__ __forceinline__ void mbar_arrive(uint32_t bar) { asm volatile("mbarrier.arrive.shared::cta.b64 _, [%0];" ::"r"(bar) : "memory"); }
__device__ __forceinline__ uint32_t mapa(uint32_t addr, uint32_t cta) {
  uint32_t r; asm("mapa.shared::cluster.u32 %0, %1, %2;" : "=r"(r) : "r"(addr), "r"(cta)); return r;
}
__device__ __forceinline__ void mbar_arrive_remote(uint32_t raddr) { asm volatile("mbarrier.arrive.release.cluster.shared::cluster.b64 _, [%0];" ::"r"(raddr) : "memory"); }
__device__ __forceinline__ bool mbar_try(uint32_t bar, uint32_t parity) {
  uint32_t ok;
  asm volatile("{\n.reg .pred p;\nmbarrier.try_wait.parity.shared::cta.b64 p, [%1], %2;\nselp.u32 %0, 1, 0, p;\n}" : "=r"(ok) : "r"(bar), "r"(parity) : "memory");
  return ok != 0;
}
__device__ __forceinline__ bool mbar_try_cl(uint32_t bar, uint32_t parity) {
  uint32_t ok;
  asm volatile("{\n.reg .pred p;\nmbarrier.try_wait.parity.acquire.cluster.shared::cta.b64 p, [%1], %2;\nselp.u32 %0, 1, 0, p;\n}" : "=r"(ok) : "r"(bar), "r"(parity) : "memory");
  return ok != 0;
}
__device__ __forceinline__ void mbar_wait(uint32_t bar, uint32_t parity, int) {
  asm volatile("{\n.reg .pred p;\n.reg .u32 c;\nmov.u32 c, 0;\n"
               "LW: mbarrier.try_wait.parity.shared::cta.b64 p, [%0], %1;\n@p bra LD;\n"
               "add.u32 c, c, 1;\nsetp.lt.u32 p, c, 0x400000;\n@p bra LW;\ntrap;\nLD:\n}" ::"r"(bar), "r"(parity) : "memory");
}
__device__ __forceinline__ void mbar_wait_cl(uint32_t bar, uint32_t parity, int) {
  asm volatile("{\n.reg .pred p;\n.reg .u32 c;\nmov.u32 c, 0;\n"
               "LW: mbarrier.try_wait.parity.acquire.cluster.shared::cta.b64 p, [%0], %1;\n@p bra LD;\n"
               "add.u32 c, c, 1;\nsetp.lt.u32 p, c, 0x400000;\n@p bra LW;\ntrap;\nLD:\n}" ::"r"(bar), "r"(parity) : "memory");
}
__device__ __forceinline__ unsigned ld_acquire(const unsigned* p) {
  unsigned v; asm volatile("ld.acquire.gpu.global.u32 %0, [%1];" : "=r"(v) : "l"(p) : "memory"); return v;
}
__device__ __forceinline__ void red_release(unsigned* p, unsigned v) { asm volatile("red.release.gpu.global.add.u32 [%0], %1;" ::"l"(p), "r"(v) : "memory"); }
__device__ __forceinline__ void fence_async_glb() { asm volatile("fence.proxy.async.global;" ::: "memory"); }
__device__ __forceinline__ void fence_async_smem() { asm volatile("fence.proxy.async.shared::cta;" ::: "memory"); }
__device__ __forceinline__ unsigned ld_epoch_raw(int cta) {
  unsigned v; asm volatile("ld.relaxed.gpu.global.u32 %0, [%1];" : "=r"(v) : "l"(g_epoch + cta * 32) : "memory"); return v;
}
__device__ __forceinline__ unsigned ld_epoch(int cta) { return ld_epoch_raw(cta) + 1; }
__device__ __forceinline__ void wait_flag(int idx, unsigned target, int site) {
  const unsigned* p = g_flags + idx * 32;
  asm volatile("{\n.reg .pred p;\n.reg .u32 c, v;\nmov.u32 c, 0;\n"
               "LW: ld.acquire.gpu.global.u32 v, [%0];\nsub.u32 v, v, %1;\nsetp.ge.s32 p, v, 0;\n@p bra LD;\n"
               "add.u32 c, c, 1;\nsetp.lt.u32 p, c, 0x200000;\n@p bra LW;\ntrap;\nLD:\n}" ::"l"(p), "r"(target) : "memory");
}
__device__ __forceinline__ uint32_t poll_mask(int idx0, int n, unsigned target, int need, int site) {
  const int lane = threadIdx.x & 31;
  const unsigned* p = g_flags + (idx0 + (lane < n ? lane : 0)) * 32;
  uint32_t m;
#pragma unroll 1
  for (uint32_t it = 0;; it++) {
    unsigned v = ld_acquire(p);
    m = __ballot_sync(0xffffffffu, (int)(v - target) >= 0);
    if ((m >> need) & 1) break;
    if (it > 0x200000u) __trap();
  }
  fence_async_glb();
  return m;
}

__device__ __forceinline__ void tma2d(uint32_t dst, const CUtensorMap* m, int c0, int c1, uint32_t bar) {
  asm volatile("cp.async.bulk.tensor.2d.shared::cluster.global.mbarrier::complete_tx::bytes [%0], [%1, {%3, %4}], [%2];"
               ::"r"(dst), "l"(m), "r"(bar), "r"(c0), "r"(c1) : "memory");
}
__device__ __forceinline__ void tma3d(uint32_t dst, const CUtensorMap* m, int c0, int c1, int c2, uint32_t bar) {
  asm volatile("cp.async.bulk.tensor.3d.shared::cluster.global.mbarrier::complete_tx::bytes [%0], [%1, {%3, %4, %5}], [%2];"
               ::"r"(dst), "l"(m), "r"(bar), "r"(c0), "r"(c1), "r"(c2) : "memory");
}
__device__ __forceinline__ void tma2d_st(const CUtensorMap* m, uint32_t src, int c0, int c1) {
  asm volatile("cp.async.bulk.tensor.2d.global.shared::cta.bulk_group [%0, {%2, %3}], [%1];" ::"l"(m), "r"(src), "r"(c0), "r"(c1) : "memory");
}
__device__ __forceinline__ void tma3d_st(const CUtensorMap* m, uint32_t src, int c0, int c1, int c2) {
  asm volatile("cp.async.bulk.tensor.3d.global.shared::cta.bulk_group [%0, {%2, %3, %4}], [%1];" ::"l"(m), "r"(src), "r"(c0), "r"(c1), "r"(c2) : "memory");
}
__device__ __forceinline__ void bulk_ld(uint32_t dst, const void* src, uint32_t bytes, uint32_t bar) {
  asm volatile("cp.async.bulk.shared::cluster.global.mbarrier::complete_tx::bytes [%0], [%1], %2, [%3];" ::"r"(dst), "l"(src), "r"(bytes), "r"(bar) : "memory");
}
__device__ __forceinline__ void bulk_commit() { asm volatile("cp.async.bulk.commit_group;" ::: "memory"); }
__device__ __forceinline__ void bulk_wait0() { asm volatile("cp.async.bulk.wait_group 0;" ::: "memory"); }
__device__ __forceinline__ void bulk_wait0_read() { asm volatile("cp.async.bulk.wait_group.read 0;" ::: "memory"); }
__device__ __forceinline__ void prefetch_map(const CUtensorMap* m) { asm volatile("prefetch.tensormap [%0];" ::"l"(m) : "memory"); }

__device__ __forceinline__ uint64_t mkdesc(uint32_t addr, uint32_t lbo, uint32_t sbo) {
  return (uint64_t)((addr & 0x3FFFF) >> 4) | ((uint64_t)(lbo >> 4) << 16) | ((uint64_t)(sbo >> 4) << 32) | (1ull << 62);
}
__device__ __forceinline__ void wg_fence() { asm volatile("wgmma.fence.sync.aligned;" ::: "memory"); }
__device__ __forceinline__ void wg_commit() { asm volatile("wgmma.commit_group.sync.aligned;" ::: "memory"); }
template <int N> __device__ __forceinline__ void wg_wait() { asm volatile("wgmma.wait_group.sync.aligned %0;" ::"n"(N) : "memory"); }
__device__ __forceinline__ void bar_sync(int id, int n) { asm volatile("bar.sync %0, %1;" ::"r"(id), "r"(n) : "memory"); }

__device__ __forceinline__ uint32_t pack2(float lo, float hi) {
  uint32_t r; asm("cvt.rn.bf16x2.f32 %0, %1, %2;" : "=r"(r) : "f"(hi), "f"(lo)); return r;
}
__device__ __forceinline__ float bf_lo(uint32_t v) { return __uint_as_float(v << 16); }
__device__ __forceinline__ float bf_hi(uint32_t v) { return __uint_as_float(v & 0xffff0000u); }
__device__ __forceinline__ float bfr(float x) { return bf_lo(pack2(x, 0.f)); }
__device__ __forceinline__ uint32_t badd2(uint32_t a, uint32_t b) { uint32_t r; asm("add.rn.bf16x2 %0, %1, %2;" : "=r"(r) : "r"(a), "r"(b)); return r; }
__device__ __forceinline__ uint32_t bsub2(uint32_t a, uint32_t b) { uint32_t r; asm("sub.rn.bf16x2 %0, %1, %2;" : "=r"(r) : "r"(a), "r"(b)); return r; }
__device__ __forceinline__ uint32_t bmul2(uint32_t a, uint32_t b) { uint32_t r; asm("mul.rn.bf16x2 %0, %1, %2;" : "=r"(r) : "r"(a), "r"(b)); return r; }
__device__ __forceinline__ uint32_t dup_bf(const bf16* p) { uint32_t v = *reinterpret_cast<const uint16_t*>(p); return v | (v << 16); }
__device__ __forceinline__ float cos_frac(int m, int n) { return __cosf((float)(2 * m > n ? m - n : m) * (6.283185307179586f / (float)n)); }
__device__ __forceinline__ float sin_frac(int m, int n) { return __sinf((float)(2 * m > n ? m - n : m) * (6.283185307179586f / (float)n)); }
__device__ __forceinline__ void stsm4(uint32_t addr, uint32_t a, uint32_t b, uint32_t c, uint32_t d) {
  asm volatile("stmatrix.sync.aligned.m8n8.x4.shared.b16 [%0], {%1, %2, %3, %4};" ::"r"(addr), "r"(a), "r"(b), "r"(c), "r"(d) : "memory");
}
__device__ __forceinline__ void stsm4t(uint32_t addr, uint32_t a, uint32_t b, uint32_t c, uint32_t d) {
  asm volatile("stmatrix.sync.aligned.m8n8.x4.trans.shared.b16 [%0], {%1, %2, %3, %4};" ::"r"(addr), "r"(a), "r"(b), "r"(c), "r"(d) : "memory");
}
__device__ __forceinline__ float gelu_tanh(float x) {
  float x2 = x * x;
  float z = x * fmaf(x2, 0.044715f * 0.7978845608028654f, 0.7978845608028654f);
  float t; asm("tanh.approx.f32 %0, %1;" : "=f"(t) : "f"(z));
  float hx = 0.5f * x;
  return fmaf(hx, t, hx);
}

__device__ __forceinline__ void row_load(const Params& P, int row0, int lane, uint32_t (&lo)[2][5], uint32_t (&hi)[2][5], uint32_t (&gl)[5], uint32_t (&gh)[5]) {
  const bool ok4 = lane < 16;
#pragma unroll
  for (int r = 0; r < 2; r++) {
    const uint32_t* x = reinterpret_cast<const uint32_t*>(P.Ax + (size_t)(row0 + r) * D_) + lane;
#pragma unroll
    for (int i = 0; i < 5; i++) {
      lo[r][i] = (i < 4 || ok4) ? __ldg(x + 32 * i) : 0u;
      hi[r][i] = (i < 4 || ok4) ? __ldg(x + 144 + 32 * i) : 0u;
    }
  }
  const uint32_t* gw = reinterpret_cast<const uint32_t*>(P.gw) + lane;
#pragma unroll
  for (int i = 0; i < 5; i++) { gl[i] = (i < 4 || ok4) ? __ldg(gw + 32 * i) : 0u; gh[i] = (i < 4 || ok4) ? __ldg(gw + 144 + 32 * i) : 0u; }
}
__device__ __forceinline__ void bar_arrive(int id, int n) { asm volatile("bar.arrive %0, %1;" ::"r"(id), "r"(n) : "memory"); }
__device__ __forceinline__ void row_job(const Params& P, int row0, int lane, const uint32_t (&lo)[2][5], const uint32_t (&hi)[2][5],
                                        const uint32_t (&gwl)[5], const uint32_t (&gwh)[5], long long t_start) {
  const bool stmp = (threadIdx.x == 128);
  if (stmp) STAMP(16);
  const bool ok4 = lane < 16;
  float s[2], q[2];
#pragma unroll
  for (int r = 0; r < 2; r++) {
    float a = 0.f, b = 0.f;
#pragma unroll
    for (int i = 0; i < 5; i++) { a += bf_lo(lo[r][i]) + bf_hi(lo[r][i]); b += bf_lo(hi[r][i]) + bf_hi(hi[r][i]); }
    s[r] = a + b;
  }
#pragma unroll
  for (int o = 16; o > 0; o >>= 1) { s[0] += __shfl_xor_sync(0xffffffffu, s[0], o); s[1] += __shfl_xor_sync(0xffffffffu, s[1], o); }
  if (stmp) STAMP(17);
#pragma unroll
  for (int r = 0; r < 2; r++) {
    s[r] *= (1.0f / 576.0f);
    float a = 0.f, b = 0.f, a4 = 0.f;
#pragma unroll
    for (int i = 0; i < 5; i++) {
      const float d0 = bf_lo(lo[r][i]) - s[r], d1 = bf_hi(lo[r][i]) - s[r], d2 = bf_lo(hi[r][i]) - s[r], d3 = bf_hi(hi[r][i]) - s[r];
      if (i < 4) { a = fmaf(d0, d0, a); b = fmaf(d1, d1, b); a = fmaf(d2, d2, a); b = fmaf(d3, d3, b); }
      else a4 = fmaf(d0, d0, d1 * d1) + fmaf(d2, d2, d3 * d3);
    }
    q[r] = a + b + (ok4 ? a4 : 0.f);
  }
#pragma unroll
  for (int o = 16; o > 0; o >>= 1) { q[0] += __shfl_xor_sync(0xffffffffu, q[0], o); q[1] += __shfl_xor_sync(0xffffffffu, q[1], o); }
#pragma unroll
  for (int r = 0; r < 2; r++) {
    const uint32_t mb = pack2(s[r], s[r]);
    const float rs = 1.0f / bfr(sqrtf(bfr(bfr(q[r] * (1.0f / 576.0f)) + 1e-5f)));
    uint32_t* h = reinterpret_cast<uint32_t*>(g_h + (size_t)(row0 + r) * D_) + lane;
#pragma unroll
    for (int i = 0; i < 5; i++) {
      const uint32_t d0 = bsub2(lo[r][i], mb), d1 = bsub2(hi[r][i], mb);
      if (i < 4 || ok4) {
        h[32 * i] = pack2(bf_lo(d0) * rs, bf_hi(d0) * rs);
        h[144 + 32 * i] = pack2(bf_lo(d1) * rs, bf_hi(d1) * rs);
      }
    }
  }
  if (stmp) STAMP(18);
  bar_arrive(5, 288);
  float z[2] = {0.f, 0.f};
#pragma unroll
  for (int i = 0; i < 5; i++) {
    const uint32_t gl = gwl[i], gh = gwh[i];
#pragma unroll
    for (int r = 0; r < 2; r++) {
      uint32_t* xb = reinterpret_cast<uint32_t*>(g_xb + (size_t)(row0 + r) * D_) + lane;
      const uint32_t p0 = bmul2(lo[r][i], gl), p1 = bmul2(hi[r][i], gh);
      z[r] += (bf_lo(p0) + bf_hi(p0)) + (bf_lo(p1) + bf_hi(p1));
      if (i < 4 || ok4) {
        xb[32 * i] = badd2(lo[r][i], hi[r][i]);
        xb[144 + 32 * i] = bsub2(lo[r][i], hi[r][i]);
      }
    }
  }
#pragma unroll
  for (int o = 16; o > 0; o >>= 1) { z[0] += __shfl_xor_sync(0xffffffffu, z[0], o); z[1] += __shfl_xor_sync(0xffffffffu, z[1], o); }
  if (lane < 2) g_gate[row0 + lane] = bfr(1.0f / (1.0f + __expf(-bfr(lane ? z[1] : z[0]))));
  if (stmp) STAMP(20);
  bar_arrive(6, 288);
}

__device__ __forceinline__ void w_job(uint32_t sb, int cta, int t3, int lane) {
  mbar_wait(sb + B_W, 0, 1);
  const int w = cta & 3, jp = cta >> 2;
  const uint32_t base = sb + SM_SIDE;
#pragma unroll 2
  for (int it = 0; it < 12; it++) {
    int idx = t3 + 96 * it;
    int ip = idx & 3, cc = idx >> 2;
    int k = cc < 144 ? 2 * cc : 2 * (cc - 144) + 1;
    uint32_t o[4];
#pragma unroll
    for (int ii = 0; ii < 2; ii++) {
#pragma unroll
      for (int e = 0; e < 2; e++) {
        uint32_t off = base + e * 4624 + ((2 * ip + ii) * DF_ + k) * 2;
        uint16_t wr, wi;
        asm volatile("ld.shared.u16 %0, [%1];" : "=h"(wr) : "r"(off));
        asm volatile("ld.shared.u16 %0, [%1];" : "=h"(wi) : "r"(off + 9248));
        o[ii * 2 + e] = (uint32_t)wr | ((uint32_t)wi << 16);
      }
    }
    uint4* dst = reinterpret_cast<uint4*>(g_Wt + (size_t)cc * 2048 + (jp * 32 + 8 * w + 2 * ip) * 2);
    *dst = make_uint4(o[0], o[1], o[2], o[3]);
  }
  if (t3 < 16) {
    const uint32_t off = base + (t3 >> 3) * 4624 + (t3 & 7) * DF_ * 2;
    uint16_t a, b, c, d;
    asm volatile("ld.shared.u16 %0, [%1];" : "=h"(a) : "r"(off));
    asm volatile("ld.shared.u16 %0, [%1];" : "=h"(b) : "r"(off + 9248));
    asm volatile("ld.shared.u16 %0, [%1];" : "=h"(c) : "r"(off + 576));
    asm volatile("ld.shared.u16 %0, [%1];" : "=h"(d) : "r"(off + 9248 + 576));
    g_W0[64 * jp + 8 * w + (t3 & 7) + 32 * (t3 >> 3)] = make_uint2((uint32_t)a | ((uint32_t)b << 16), (uint32_t)c | ((uint32_t)d << 16));
  }
  __syncwarp();
  if (lane == 0) { red_release(g_flags + FL_WT * 32, 1u); mbar_arrive(sb + B_AUX); }
}

__device__ __forceinline__ void tf_gen(int gt  , int lane) {
#pragma unroll 1
  for (int idx = gt; idx < 576 * 144; idx += 6144) {
    const int kr = idx / 144, d = 2 * (idx - kr * 144);
    const int k = kr < 288 ? (kr & ~1) : (((kr - 288) & ~1) + 1);
    int m0 = (d * k) % 576, m1 = m0 + k;
    if (m1 >= 576) m1 -= 576;
    if (kr == 1) { m0 = 0; m1 = 288; }
    if ((kr & 1) && kr != 1) { m0 += 144; m1 += 144; if (m0 >= 576) m0 -= 576; if (m1 >= 576) m1 -= 576; }
    reinterpret_cast<uint32_t*>(g_TF)[idx] = pack2(cos_frac(m0, 576), cos_frac(m1, 576));
  }
  __syncwarp();
  if (lane == 0) red_release(g_flags + FL_TF * 32, 1u);
}

__global__ void __launch_bounds__(NTHREADS, 1) mega_kernel(const __grid_constant__ Params P) {
  extern __shared__ __align__(1024) uint8_t smem_raw[];
  const uint32_t sb = smem_u32(smem_raw);
  const int tid = threadIdx.x, warp = tid >> 5, lane = tid & 31;
  const int cta = blockIdx.x;
  const uint32_t rank = cta & 1;
  const long long t_start = 0;
  uint32_t xlo[2][5], xhi[2][5], gwl[5], gwh[5];
  if (warp >= 4 && cta < 128) row_load(P, cta * 16 + (warp - 4) * 2, lane, xlo, xhi, gwl, gwh);
  if (tid == 0) {
    if (sb & 1023u) __trap();
    for (int i = 0; i < 4; i++) { mbar_init(sb + B_FULL + 8 * i, 1); mbar_init(sb + B_EMPTY + 8 * i, 8); }
    mbar_init(sb + B_X, 1); mbar_init(sb + B_PFREE, 1); mbar_init(sb + B_LFREE, 8);
    mbar_init(sb + B_W, 1); mbar_init(sb + B_AUX, 3);
    for (int i = 0; i < 4; i++) mbar_init(sb + B_F2 + 8 * i, 1);
    mbar_expect_tx(sb + B_X, 49152);
    asm volatile("fence.mbarrier_init.release.cluster;" ::: "memory");
  }
  __syncthreads();
  asm volatile("barrier.cluster.arrive.relaxed.aligned;" ::: "memory");

  const bool isG = cta < NG;
  const int cl = cta >> 1;
  const int gj = cl / 18, gp = cl % 18;
  const int fc = cta - NG;

  if (warp < 4) {
    asm volatile("setmaxnreg.dec.sync.aligned.u32 56;");
    if (warp == 0) {
      const unsigned ep1 = ld_epoch(cta);
      uint32_t st = 0, ph = 1;
      if (isG) {
        if (lane == 0) { prefetch_map(&P.tW1); prefetch_map(&P.tH); prefetch_map(&P.tW2); prefetch_map(&P.tU); }
        const int ft = gp + 18 * rank;
        if (lane == 0) {
          for (int s = 0; s < 4; s++) {
            mbar_expect_tx(sb + B_FULL + 8 * s, STAGE_BYTES);
            tma2d(sb + s * STAGE_BYTES, &P.tW1, ft * 128, s * 64, sb + B_FULL + 8 * s);
            tma2d(sb + s * STAGE_BYTES + 8192, &P.tW1, ft * 128 + 64, s * 64, sb + B_FULL + 8 * s);
          }
        }
        uint32_t ready = 0;
#pragma unroll 1
        for (int kb = 0; kb < 32; kb++) {
          const uint32_t sa = sb + st * STAGE_BYTES, fb = sb + B_FULL + 8 * st;
          if (kb >= 4) {
            mbar_wait(sb + B_EMPTY + 8 * st, ph, 2);
            if (lane == 0) {
              mbar_expect_tx(fb, STAGE_BYTES);
              tma2d(sa, &P.tW1, ft * 128, kb * 64, fb);
              tma2d(sa + 8192, &P.tW1, ft * 128 + 64, kb * 64, fb);
            }
          }
          if (!((ready >> kb) & 1)) { ready = poll_mask(FL_H, 32, ep1 * 4, kb, 3); if (kb == 0 && lane == 0) STAMP(23); }
          if (lane == 0) {
#pragma unroll
            for (int i = 0; i < 3; i++) tma2d(sa + 16384 + i * 8192, &P.tH, gj * 192 + i * 64, kb * 64, fb);
          }
          __syncwarp();
          if (++st == 4) { st = 0; ph ^= 1; }
        }
        if (lane == 0) STAMP(8);
        if (gp < 16) {
          ready = 0;
#pragma unroll 1
          for (int i2 = 0; i2 < 36; i2++) {
            const int n2 = i2 >> 1;
            const int tl = n2 == 0 ? gp : (n2 - 1 < gp ? n2 - 1 : n2);
            const int f0 = (18 * rank + tl) * 128 + (i2 & 1) * 64;
            const uint32_t sa = sb + st * STAGE_BYTES, fb = sb + B_FULL + 8 * st;
            mbar_wait(sb + B_EMPTY + 8 * st, ph, 4);
            if (lane == 0) {
              mbar_expect_tx(fb, i2 < 2 ? 16384 : STAGE_BYTES);
              tma2d(sa, &P.tW2, gp * 128, f0, fb);
              tma2d(sa + 8192, &P.tW2, gp * 128 + 64, f0, fb);
            }
            if (i2 >= 2) {
              if (!((ready >> tl) & 1)) ready = poll_mask(FL_U + gj * 36 + 18 * rank, 18, ep1, tl, 5);
              if (lane == 0) {
#pragma unroll
                for (int i = 0; i < 3; i++) tma2d(sa + 16384 + i * 8192, &P.tU, gj * 192 + i * 64, f0, fb);
              }
            }
            __syncwarp();
            if (++st == 4) { st = 0; ph ^= 1; }
          }
        }
      } else {
        if (lane == 0) {
          prefetch_map(&P.tXB); prefetch_map(&P.tTFk); prefetch_map(&P.tX1c); prefetch_map(&P.tZT); prefetch_map(&P.tTFn);
          wait_flag(FL_TF, ep1 * 192, 6);
#pragma unroll 1
          for (int it = 0; it < 4; it++) {
            const int item = fc + 24 * it, sblk = item & 15, nb = item >> 4;
            wait_flag(FL_XB + sblk, ep1 * 8, 7);
            fence_async_glb();
#pragma unroll 1
            for (int kb = 0; kb < 5; kb++) {
              const uint32_t sa = sb + st * STAGE_BYTES, fb = sb + B_FULL + 8 * st;
              mbar_wait(sb + B_EMPTY + 8 * st, ph, 8);
              mbar_expect_tx(fb, 16384 + 12288);
              tma2d(sa, &P.tXB, (nb >= 3 ? 288 : 0) + kb * 64, sblk * 128, fb);
              tma2d(sa + 16384, &P.tTFk, kb * 64, nb * 96, fb);
              if (++st == 4) { st = 0; ph ^= 1; }
            }
          }
          STAMP(8);
          wait_flag(FL_X1, ep1 * 48, 9);
          fence_async_glb();
#pragma unroll 1
          for (int b = 0; b < 2; b++)
#pragma unroll 1
            for (int w = 0; w < 2; w++) {
              const uint32_t bar = sb + B_F2 + 8 * (w * 2 + b);
              mbar_expect_tx(bar, 24576);
              for (int c = 0; c < 3; c++) {
                const int cc = w * 144 + fc * 6 + b * 3 + c;
                tma3d(sb + w * 65536 + (b * 3 + c) * 8192, &P.tX1c, 0, 0, 2 * cc, bar);
              }
            }
          STAMP(9);
          wait_flag(FL_Z, ep1 * 48, 10);
          fence_async_glb();
          STAMP(10);
#pragma unroll 1
          for (int it = 0; it < 2; it++) {
            const int item = fc + 24 * it, sblk = item & 15, q = item >> 4;
#pragma unroll 1
            for (int k2 = 0; k2 < 10; k2++) {
              const int krow = (k2 >= 5 ? 288 + (k2 - 5) * 64 : k2 * 64);
              const uint32_t sa = sb + st * STAGE_BYTES, fb = sb + B_FULL + 8 * st;
              mbar_wait(sb + B_EMPTY + 8 * st, ph, 11);
              mbar_expect_tx(fb, 32768);
              tma2d(sa, &P.tZT, sblk * 128, krow, fb);
              tma2d(sa + 8192, &P.tZT, sblk * 128 + 64, krow, fb);
              tma2d(sa + 16384, &P.tTFn, q * 96, krow, fb);
              tma2d(sa + 24576, &P.tTFn, q * 96 + 64, krow, fb);
              if (++st == 4) { st = 0; ph ^= 1; }
            }
          }
        }
        __syncwarp();
      }
    } else {
      if (cta < 128) {
        if (warp == 2) {
          bar_sync(5, 288);
          if (lane == 0) { STAMP(21); red_release(g_flags + (FL_H + (cta >> 2)) * 32, 1u); STAMP(22); }
          bar_sync(6, 288);
          if (lane == 0) {
            red_release(g_flags + (FL_XB + (cta >> 3)) * 32, 1u);
            const int j0 = 64 * (cta >> 2) + 8 * (cta & 3);
            mbar_expect_tx(sb + B_W, 4 * 4624);
            bulk_ld(sb + SM_SIDE, P.Wr + (size_t)j0 * DF_, 4624, sb + B_W);
            bulk_ld(sb + SM_SIDE + 4624, P.Wr + (size_t)(j0 + 32) * DF_, 4624, sb + B_W);
            bulk_ld(sb + SM_SIDE + 9248, P.Wi + (size_t)j0 * DF_, 4624, sb + B_W);
            bulk_ld(sb + SM_SIDE + 13872, P.Wi + (size_t)(j0 + 32) * DF_, 4624, sb + B_W);
          }
          __syncwarp();
        }
        w_job(sb, cta, tid - 32, lane);
      } else if (lane == 0) {
        mbar_arrive(sb + B_AUX);
      }
      if (lane == 0) STAMP(11 + warp);
      if (warp == 1 && isG) {
        bar_sync(1, 288);
        if (lane == 0) {
          const int ft = gp + 18 * rank;
#pragma unroll
          for (int w = 0; w < 2; w++)
#pragma unroll
            for (int i = 0; i < 3; i++) tma2d_st(&P.tU, sb + SM_STG + w * 24576 + i * 8192, gj * 192 + i * 64, ft * 128 + w * 64);
          bulk_commit();
          bulk_wait0();
          fence_async_glb();
          red_release(g_flags + (FL_U + gj * 36 + ft) * 32, 1u);
          STAMP(15);
          if (gp < 16) {
            mbar_wait(sb + B_LFREE, 0, 12);
            asm volatile("barrier.cluster.wait.acquire;" ::: "memory");
            mbar_arrive_remote(mapa(sb + B_PFREE, rank ^ 1));
          }
        }
      }
    }
  } else {
    asm volatile("setmaxnreg.inc.sync.aligned.u32 224;");
    const int cw = warp - 4;
    const int wg = cw >> 2, wq = cw & 3;
    const int ct = tid - 128;
    const int q4 = lane & 3, r8 = lane >> 2;
    const unsigned ep0 = ld_epoch_raw(cta);
    if (cta < 128) row_job(P, cta * 16 + cw * 2, lane, xlo, xhi, gwl, gwh, t_start);
    if (ct == 0) STAMP(0);
    unsigned ep1;
    asm volatile("add.u32 %0, %1, 1;" : "=r"(ep1) : "r"(ep0));
    uint32_t st = 0, ph = 0;
    if (isG) {
      const int ft = gp + 18 * rank;
      const uint32_t bias0 = dup_bf(P.b1 + ft * 128 + wg * 64 + wq * 16 + r8), bias1 = dup_bf(P.b1 + ft * 128 + wg * 64 + wq * 16 + r8 + 8);
      float acc[96];
      const uint64_t dA0 = mkdesc(sb + wg * 8192, 8192, 1024), dB0 = mkdesc(sb + 16384, 8192, 1024);
      uint32_t prev = 0;
#pragma unroll 1
      for (int kb = 0; kb < 32; kb++) {
        mbar_wait(sb + B_FULL + 8 * st, ph, 13);
        if (kb == 0 && ct == 0) STAMP(1);
        const uint64_t so = (uint64_t)(st * (STAGE_BYTES >> 4));
        wg_fence();
#pragma unroll
        for (int kk = 0; kk < 4; kk++) wg_ss_n192<1, 1>(acc, dA0 + so + kk * 128, dB0 + so + kk * 128, (kb | kk) != 0);
        wg_commit();
        if (kb > 0) { wg_wait<1>(); if (lane == 0) mbar_arrive(sb + B_EMPTY + 8 * prev); }
        prev = st;
        if (++st == 4) { st = 0; ph ^= 1; }
      }
      wg_wait<0>();
      if (lane == 0) mbar_arrive(sb + B_EMPTY + 8 * prev);
      if (ct == 0) STAMP(2);
      {
        const int jm = lane >> 3, i8 = lane & 7;
        const uint32_t row = wq * 16 + (jm & 1) * 8 + i8;
        const uint32_t base = sb + SM_STG + wg * 24576 + row * 128;
#pragma unroll
        for (int G = 0; G < 24; G += 2) {
          uint32_t r[4];
#pragma unroll
          for (int m = 0; m < 4; m++) {
            const uint32_t x = badd2(pack2(acc[4 * G + 2 * m], acc[4 * G + 2 * m + 1]), (m & 1) ? bias1 : bias0);
            r[m] = pack2(gelu_tanh(bf_lo(x)), gelu_tanh(bf_hi(x)));
          }
          const uint32_t grp = G + (jm >> 1);
          stsm4(base + (grp >> 3) * 8192 + (((grp & 7) ^ i8) << 4), r[0], r[1], r[2], r[3]);
        }
      }
      fence_async_smem();
      bar_sync(1, 288);
      if (ct == 0) STAMP(3);
      if (gp < 16) {
        const uint64_t dS0 = mkdesc(sb + SM_STG, 8192, 1024);
#pragma unroll 1
        for (int i2 = 0; i2 < 36; i2++) {
          mbar_wait(sb + B_FULL + 8 * st, ph, 14);
          const uint64_t so = (uint64_t)(st * (STAGE_BYTES >> 4));
          const uint64_t db = i2 < 2 ? dS0 + (uint64_t)(i2 * (24576 >> 4)) : dB0 + so;
          wg_fence();
#pragma unroll
          for (int kk = 0; kk < 4; kk++) wg_ss_n192<1, 1>(acc, dA0 + so + kk * 128, db + kk * 128, (i2 | kk) != 0);
          wg_commit();
          if (i2 > 0) {
            wg_wait<1>();
            if (lane == 0) { mbar_arrive(sb + B_EMPTY + 8 * prev); if (i2 == 2) mbar_arrive(sb + B_LFREE); }
          }
          if (ct == 0 && (i2 == 2 || i2 == 3 || i2 == 4 || i2 == 8 || i2 == 16)) STAMP(i2 == 2 ? 24 : i2 == 3 ? 25 : i2 == 4 ? 26 : i2 == 8 ? 27 : 28);
          prev = st;
          if (++st == 4) { st = 0; ph ^= 1; }
        }
        wg_wait<0>();
        if (ct == 0) STAMP(4);
        asm volatile("barrier.cluster.wait.acquire;" ::: "memory");
        mbar_wait_cl(sb + B_PFREE, 0, 15);
        {
          const uint32_t rdst = mapa(sb + SM_STG + ct * 16, rank ^ 1), rbar = mapa(sb + B_X, rank ^ 1);
          if (rank == 0) {
#pragma unroll
            for (int i = 0; i < 12; i++)
              asm volatile("st.async.weak.shared::cluster.mbarrier::complete_tx::bytes.v4.f32 [%0], {%1, %2, %3, %4}, [%5];"
                           ::"r"(rdst + i * 4096), "f"(acc[48 + 4 * i]), "f"(acc[49 + 4 * i]), "f"(acc[50 + 4 * i]), "f"(acc[51 + 4 * i]), "r"(rbar) : "memory");
          } else {
#pragma unroll
            for (int i = 0; i < 12; i++)
              asm volatile("st.async.weak.shared::cluster.mbarrier::complete_tx::bytes.v4.f32 [%0], {%1, %2, %3, %4}, [%5];"
                           ::"r"(rdst + i * 4096), "f"(acc[4 * i]), "f"(acc[1 + 4 * i]), "f"(acc[2 + 4 * i]), "f"(acc[3 + 4 * i]), "r"(rbar) : "memory");
#pragma unroll
            for (int i = 0; i < 48; i++) acc[i] = acc[48 + i];
          }
        }
        const int cb = 2 * gj + rank;
        const int srow = gp * 128 + wg * 64 + wq * 16 + r8;
        if (lane == 0) { wait_flag(FL_XB + gp, ep1 * 8, 16); wait_flag(FL_A + gp * 3 + (cb % 3), ep1 * 8, 17); }
        __syncwarp();
        uint4 af[6];
#pragma unroll
        for (int i = 0; i < 6; i++) af[i] = __ldcg(g_afrag + ((size_t)(gp * 6 + cb) * 6 + i) * 256 + ct);
        const float gf0 = __ldcg(g_gate + srow), gf1 = __ldcg(g_gate + srow + 8);
        const uint32_t g0 = pack2(gf0, gf0), g1 = pack2(gf1, gf1), og0 = pack2(1.0f - gf0, 1.0f - gf0), og1 = pack2(1.0f - gf1, 1.0f - gf1);
        const uint32_t c0 = dup_bf(P.b2 + srow), c1 = dup_bf(P.b2 + srow + 8);
        bar_sync(4, 256);
        mbar_wait_cl(sb + B_X, 0, 18);
        if (ct == 0) STAMP(5);
        {
          const int jm = lane >> 3, i8 = lane & 7;
          const uint32_t row = wq * 16 + (jm & 1) * 8 + i8;
          const uint32_t obase = sb + wg * 12288 + row * 64;
#pragma unroll
          for (int i = 0; i < 6; i++) {
            float v[8];
#pragma unroll
            for (int hh = 0; hh < 2; hh++) {
              float4 pz;
              asm volatile("ld.shared.v4.f32 {%0, %1, %2, %3}, [%4];" : "=f"(pz.x), "=f"(pz.y), "=f"(pz.z), "=f"(pz.w) : "r"(sb + SM_STG + ct * 16 + (2 * i + hh) * 4096));
              v[4 * hh] = acc[8 * i + 4 * hh] + pz.x; v[4 * hh + 1] = acc[8 * i + 4 * hh + 1] + pz.y;
              v[4 * hh + 2] = acc[8 * i + 4 * hh + 2] + pz.z; v[4 * hh + 3] = acc[8 * i + 4 * hh + 3] + pz.w;
            }
            const uint32_t aw[4] = {af[i].x, af[i].y, af[i].z, af[i].w};
            uint32_t r[4];
#pragma unroll
            for (int m = 0; m < 4; m++) {
              const uint32_t bb = badd2(pack2(v[2 * m], v[2 * m + 1]), (m & 1) ? c1 : c0);
              r[m] = badd2(bmul2((m & 1) ? g1 : g0, aw[m]), bmul2((m & 1) ? og1 : og0, bb));
            }
            const uint32_t grp = 2 * i + (jm >> 1);
            stsm4(obase + (grp >> 2) * 4096 + (((grp & 3) ^ ((row >> 1) & 3)) << 4), r[0], r[1], r[2], r[3]);
          }
        }
        fence_async_smem();
        bar_sync(2 + wg, 128);
        if ((ct & 127) == 0) {
#pragma unroll
          for (int i = 0; i < 3; i++) tma2d_st(&P.tOut, sb + wg * 12288 + i * 4096, cb * 96 + i * 32, gp * 128 + wg * 64);
          bulk_commit();
          bulk_wait0_read();
        }
        if (ct == 0) STAMP(6);
      }
      if (ct == 0) g_epoch[cta * 32] = ep1;
    } else {
      tf_gen(fc * 256 + ct, lane);
      if (ct == 0) STAMP(1);
      const int jm = lane >> 3, i8 = lane & 7;
      {
        const uint64_t dA0 = mkdesc(sb + wg * 8192, 16, 1024), dB0 = mkdesc(sb + 16384, 16, 1024);
        float acc[48];
#pragma unroll 1
        for (int it = 0; it < 4; it++) {
          const int item = fc + 24 * it, sblk = item & 15, nb = item >> 4;
          uint32_t prev = 0;
#pragma unroll 1
          for (int kb = 0; kb < 5; kb++) {
            mbar_wait(sb + B_FULL + 8 * st, ph, 19);
            if (ct == 0 && it == 1 && kb == 0) STAMP(29);
            if (ct == 0 && it == 1 && kb == 4) STAMP(30);
            const uint64_t so = (uint64_t)(st * (STAGE_BYTES >> 4));
            wg_fence();
            wg_ss_n96<0, 0>(acc, dA0 + so, dB0 + so, kb != 0);
            wg_ss_n96<0, 0>(acc, dA0 + so + 2, dB0 + so + 2, 1);
            if (kb < 4) { wg_ss_n96<0, 0>(acc, dA0 + so + 4, dB0 + so + 4, 1); wg_ss_n96<0, 0>(acc, dA0 + so + 6, dB0 + so + 6, 1); }
            wg_commit();
            if (kb > 0) { wg_wait<1>(); if (lane == 0) mbar_arrive(sb + B_EMPTY + 8 * prev); }
            prev = st;
            if (++st == 4) { st = 0; ph ^= 1; }
          }
          wg_wait<0>();
          if (lane == 0) mbar_arrive(sb + B_EMPTY + 8 * prev);
          if ((ct & 127) == 0) bulk_wait0_read();
          bar_sync(2 + wg, 128);
          const uint32_t base = sb + SM_STG + wg * 12288;
#pragma unroll
          for (int G = 0; G < 12; G += 2) {
            const uint32_t row = 8 * (G + (jm >> 1)) + i8;
            stsm4t(base + row * 128 + (((2 * wq + (jm & 1)) ^ i8) << 4), pack2(acc[4 * G], acc[4 * G + 1]), pack2(acc[4 * G + 2], acc[4 * G + 3]),
                   pack2(acc[4 * G + 4], acc[4 * G + 5]), pack2(acc[4 * G + 6], acc[4 * G + 7]));
          }
          fence_async_smem();
          bar_sync(2 + wg, 128);
          if ((ct & 127) == 0) { tma2d_st(&P.tX1s, base, sblk * 128 + wg * 64, nb * 96); bulk_commit(); }
          if (ct == 0) STAMP(25 + it);
        }
        if ((ct & 127) == 0) { bulk_wait0(); fence_async_glb(); red_release(g_flags + FL_X1 * 32, 1u); }
      }
      if (ct == 0) STAMP(2);
      {
        mbar_wait(sb + B_AUX, 0, 20);
#pragma unroll 1
        for (int idx = ct; idx < 128 * 32; idx += 256) {
          const int n = idx >> 5, k = (idx & 31) * 2;
          const int g = n >> 3, qq = (n >> 1) & 3;
          const int pi = 16 * (g >> 2) + 8 * ((g >> 1) & 1) + 2 * qq + (g & 1);
          const int sh = (n & 1) * 48;
          const uint32_t addr = sb + SM_SIDE + n * 128 + (((k >> 3) ^ (n & 7)) << 4) + (k & 7) * 2;
          asm volatile("st.shared.u32 [%0], %1;" ::"r"(addr), "r"(pack2(cos_frac((k * pi + sh) & 63, 64), cos_frac(((k + 1) * pi + sh) & 63, 64))) : "memory");
        }
        const int j1 = 8 * wq + r8;
        const uint32_t atab = sb + SM_STG + 24576 + (ct & 127) * 16;
#pragma unroll 1
        for (int tm = 0; tm < 16; tm++) {
          const int m = tm & 3, k0 = 16 * (tm >> 2) + 8 * (m >> 1) + 2 * q4;
          float v[2];
#pragma unroll
          for (int e = 0; e < 2; e++) {
            const int k = k0 + e;
            int an, rip, ri;
            if (wg == 0) {
              an = j1 * (k & 31); rip = m & 1; ri = k >> 5;
              an += (rip == ri) ? 0 : (rip ? 8 : 24);
            } else {
              const int row = 16 * wq + 8 * (m & 1) + r8;
              rip = row >> 5; ri = (k >> 3) & 1;
              an = (row & 31) * (8 * (k >> 4) + (k & 7));
              an += (rip == ri) ? 0 : (rip ? 24 : 8);
            }
            v[e] = cos_frac(an & 31, 32);
          }
          asm volatile("st.shared.b32 [%0], %1;" ::"r"(atab + wg * 8192 + (tm >> 2) * 2048 + m * 4), "r"(pack2(v[0], v[1])) : "memory");
        }
        float twc[16], tws[16];
#pragma unroll
        for (int i = 0; i < 16; i++) {
          const int an = j1 * (8 * (i >> 1) + 2 * q4 + (i & 1));
          twc[i] = cos_frac(an, 2048); tws[i] = sin_frac(an, 2048);
        }
        fence_async_smem();
        if (lane == 0) wait_flag(FL_WT, ep1 * 384, 21);
        bar_sync(4, 256);
        const uint64_t dC = mkdesc(sb + SM_SIDE, 16, 1024);
        const uint32_t wbase = sb + wg * 65536;
        const uint32_t strow = (16 * wq + 8 * (jm & 1) + i8) * 128;
        constexpr float SCALE = 2.0f / (2048.0f * 576.0f);
#pragma unroll 1
        for (int c = 0; c < 6; c++) {
          const uint32_t xbuf = wbase + c * 8192, tbuf = wbase + 49152 + (c & 1) * 8192;
          const int cc = wg * 144 + fc * 6 + c;
          uint2 Wv[8];
          {
            const uint2* wp = reinterpret_cast<const uint2*>(g_Wt + (size_t)cc * 2048) + q4 * 32 + j1;
#pragma unroll
            for (int G = 0; G < 8; G++) Wv[G] = __ldcg(wp + G * 128);
          }
          uint32_t A[16];
#pragma unroll
          for (int t = 0; t < 4; t++)
            asm volatile("ld.shared.v4.b32 {%0, %1, %2, %3}, [%4];" : "=r"(A[4 * t]), "=r"(A[4 * t + 1]), "=r"(A[4 * t + 2]), "=r"(A[4 * t + 3]) : "r"(atab + t * 2048));
          if (c == 0 || c == 3) mbar_wait(sb + B_F2 + 8 * (wg * 2 + (c != 0)), 0, 22);
          const bool stm = (ct == 0 && c == 2);
          if (stm) STAMP(16);
          {
            float acc[32];
            const uint64_t dX = mkdesc(xbuf, 8192, 1024);
            wg_fence();
#pragma unroll
            for (int t = 0; t < 4; t++) wg_rs_n64<1>(acc, A[4 * t], A[4 * t + 1], A[4 * t + 2], A[4 * t + 3], dX + t * 128, t != 0);
            wg_commit();
            wg_wait<0>();
#pragma unroll
            for (int G = 0; G < 8; G++) {
              const float* a = &acc[4 * G];
              const float c0 = twc[2 * G], s0 = tws[2 * G], c1 = twc[2 * G + 1], s1 = tws[2 * G + 1];
              A[4 * (G >> 1) + 2 * (G & 1)] = pack2(a[0] * c0 + a[2] * s0, a[1] * c1 + a[3] * s1);
              A[4 * (G >> 1) + 2 * (G & 1) + 1] = pack2(a[2] * c0 - a[0] * s0, a[3] * c1 - a[1] * s1);
            }
          }
          float acc[64];
          if (stm) STAMP(17);
          wg_fence();
#pragma unroll
          for (int t = 0; t < 4; t++) wg_rs_n128<0>(acc, A[4 * t], A[4 * t + 1], A[4 * t + 2], A[4 * t + 3], dC + t * 2, t != 0);
          wg_commit();
          wg_wait<0>();
          if (stm) STAMP(18);
          if (cc == 0) {
            const uint32_t scr = sb + 131072;
#pragma unroll
            for (int g = 0; g < 16; g++) {
              const int j = j1 + 32 * (8 * (g >> 1) + 2 * q4 + (g & 1));
              asm volatile("st.shared.v2.f32 [%0], {%1, %2};" ::"r"(scr + j * 8), "f"(acc[4 * g] + acc[4 * g + 3]), "f"(acc[4 * g + 2] - acc[4 * g + 1]) : "memory");
            }
            bar_sync(2 + wg, 128);
#pragma unroll
            for (int G = 0; G < 8; G++) {
              float pr[2], pi[2];
#pragma unroll
              for (int e = 0; e < 2; e++) {
                const int g = 2 * G + e;
                const int j = j1 + 32 * (8 * G + 2 * q4 + e), jn = (S_ - j) & (S_ - 1);
                float nr, ni;
                asm volatile("ld.shared.v2.f32 {%0, %1}, [%2];" : "=f"(nr), "=f"(ni) : "r"(scr + jn * 8));
                const uint2 wa = __ldcg(g_W0 + j), wb = __ldcg(g_W0 + jn);
                const float h0r = bf_lo(wa.x) + bf_lo(wb.x), h0i = bf_hi(wa.x) - bf_hi(wb.x), h1r = bf_lo(wa.y) + bf_lo(wb.y), h1i = bf_hi(wa.y) - bf_hi(wb.y);
                const float4 uv = make_float4(0.125f * (h0r + h1r), 0.125f * (h0i + h1i), 0.125f * (h0r - h1r), 0.125f * (h0i - h1i));
                const float xr = acc[4 * g] + acc[4 * g + 3], xi = acc[4 * g + 2] - acc[4 * g + 1];
                pr[e] = uv.x * xr - uv.y * xi + uv.z * nr + uv.w * ni;
                pi[e] = uv.x * xi + uv.y * xr + uv.w * nr - uv.z * ni;
              }
              A[4 * (G >> 1) + 2 * (G & 1)] = pack2(pr[0], pr[1]);
              A[4 * (G >> 1) + 2 * (G & 1) + 1] = pack2(pi[0], pi[1]);
            }
          } else {
#pragma unroll
            for (int G = 0; G < 8; G++) {
              const float* a = &acc[8 * G];
              const float x0r = a[0] + a[3], x0i = a[2] - a[1], x1r = a[4] + a[7], x1i = a[6] - a[5];
              const float w0r = bf_lo(Wv[G].x), w0i = bf_hi(Wv[G].x), w1r = bf_lo(Wv[G].y), w1i = bf_hi(Wv[G].y);
              A[4 * (G >> 1) + 2 * (G & 1)] = pack2(x0r * w0r - x0i * w0i, x1r * w1r - x1i * w1i);
              A[4 * (G >> 1) + 2 * (G & 1) + 1] = pack2(x0r * w0i + x0i * w0r, x1r * w1i + x1i * w1r);
            }
          }
          if (stm) STAMP(19);
          wg_fence();
#pragma unroll
          for (int t = 0; t < 4; t++) wg_rs_n128<0>(acc, A[4 * t], A[4 * t + 1], A[4 * t + 2], A[4 * t + 3], dC + t * 2, t != 0);
          wg_commit();
#pragma unroll
          for (int t = 0; t < 4; t++)
            asm volatile("ld.shared.v4.b32 {%0, %1, %2, %3}, [%4];" : "=r"(Wv[2 * t].x), "=r"(Wv[2 * t].y), "=r"(Wv[2 * t + 1].x), "=r"(Wv[2 * t + 1].y) : "r"(atab + 8192 + t * 2048));
          wg_wait<0>();
          if (stm) STAMP(20);
#pragma unroll
          for (int G = 0; G < 8; G += 2) {
            uint32_t r[4];
#pragma unroll
            for (int h = 0; h < 2; h++) {
              const float* a = &acc[8 * (G + h)];
              const float v0r = (a[0] - a[3]) * SCALE, v0i = (a[2] + a[1]) * SCALE, v1r = (a[4] - a[7]) * SCALE, v1i = (a[6] + a[5]) * SCALE;
              const float c0 = twc[2 * (G + h)], s0 = tws[2 * (G + h)], c1 = twc[2 * (G + h) + 1], s1 = tws[2 * (G + h) + 1];
              r[2 * h] = pack2(v0r * c0 - v0i * s0, v1r * c1 - v1i * s1);
              r[2 * h + 1] = pack2(v0i * c0 + v0r * s0, v1i * c1 + v1r * s1);
            }
            stsm4(tbuf + strow + (((G + (jm >> 1)) ^ i8) << 4), r[0], r[1], r[2], r[3]);
          }
          if (stm) STAMP(21);
          fence_async_smem();
          if (stm) STAMP(22);
          bar_sync(2 + wg, 128);
          if (stm) STAMP(23);
          if (c > 0 && (ct & 127) == 0) { tma3d_st(&P.tZc, xbuf - 8192, 0, 0, 2 * (cc - 1)); bulk_commit(); }
          {
            float ac2[32];
            const uint64_t dT = mkdesc(tbuf, 8192, 1024);
            wg_fence();
#pragma unroll
            for (int t = 0; t < 4; t++) wg_rs_n64<1>(ac2, Wv[2 * t].x, Wv[2 * t].y, Wv[2 * t + 1].x, Wv[2 * t + 1].y, dT + t * 128, t != 0);
            wg_commit();
            wg_wait<0>();
#pragma unroll
            for (int G = 0; G < 8; G += 2) {
              const float* a = &ac2[4 * G];
              stsm4(xbuf + strow + (((G + (jm >> 1)) ^ i8) << 4), pack2(a[0], a[1]), pack2(a[2], a[3]), pack2(a[4], a[5]), pack2(a[6], a[7]));
            }
          }
          if (stm) STAMP(24);
        }
        fence_async_smem();
        bar_sync(2 + wg, 128);
        if ((ct & 127) == 0) {
          tma3d_st(&P.tZc, wbase + 5 * 8192, 0, 0, 2 * (wg * 144 + fc * 6 + 5));
          bulk_commit(); bulk_wait0(); fence_async_glb(); red_release(g_flags + FL_Z * 32, 1u);
        }
      }
      if (ct == 0) STAMP(3);
      {
        const uint64_t dA0 = mkdesc(sb + wg * 8192, 8192, 1024), dB0 = mkdesc(sb + 16384, 8192, 1024);
#pragma unroll 1
        for (int it = 0; it < 2; it++) {
          const int item = fc + 24 * it, sblk = item & 15, q = item >> 4;
          float ev[48], od[48];
          uint32_t prev = 0;
#define F3_PART(ACC, FIRST)                                                                                                        \
          _Pragma("unroll 1") for (int kb = 0; kb < 5; kb++) {                                                                     \
            mbar_wait(sb + B_FULL + 8 * st, ph, 23);                                                                               \
            const uint64_t so = (uint64_t)(st * (STAGE_BYTES >> 4));                                                               \
            wg_fence();                                                                                                            \
            wg_ss_n96<1, 1>(ACC, dA0 + so, dB0 + so, kb != 0);                                                                     \
            wg_ss_n96<1, 1>(ACC, dA0 + so + 128, dB0 + so + 128, 1);                                                               \
            if (kb < 4) { wg_ss_n96<1, 1>(ACC, dA0 + so + 256, dB0 + so + 256, 1); wg_ss_n96<1, 1>(ACC, dA0 + so + 384, dB0 + so + 384, 1); } \
            wg_commit();                                                                                                           \
            if (!(FIRST) || kb > 0) { wg_wait<1>(); if (lane == 0) mbar_arrive(sb + B_EMPTY + 8 * prev); }                         \
            prev = st;                                                                                                             \
            if (++st == 4) { st = 0; ph ^= 1; }                                                                                    \
          }
          F3_PART(ev, true)
          F3_PART(od, false)
          wg_wait<0>();
          if (lane == 0) mbar_arrive(sb + B_EMPTY + 8 * prev);
#pragma unroll
          for (int i = 0; i < 6; i++) {
            uint4 p, m;
            p.x = pack2(ev[8 * i] + od[8 * i], ev[8 * i + 1] + od[8 * i + 1]); m.x = pack2(ev[8 * i] - od[8 * i], ev[8 * i + 1] - od[8 * i + 1]);
            p.y = pack2(ev[8 * i + 2] + od[8 * i + 2], ev[8 * i + 3] + od[8 * i + 3]); m.y = pack2(ev[8 * i + 2] - od[8 * i + 2], ev[8 * i + 3] - od[8 * i + 3]);
            p.z = pack2(ev[8 * i + 4] + od[8 * i + 4], ev[8 * i + 5] + od[8 * i + 5]); m.z = pack2(ev[8 * i + 4] - od[8 * i + 4], ev[8 * i + 5] - od[8 * i + 5]);
            p.w = pack2(ev[8 * i + 6] + od[8 * i + 6], ev[8 * i + 7] + od[8 * i + 7]); m.w = pack2(ev[8 * i + 6] - od[8 * i + 6], ev[8 * i + 7] - od[8 * i + 7]);
            g_afrag[((size_t)(sblk * 6 + q) * 6 + i) * 256 + ct] = p;
            g_afrag[((size_t)(sblk * 6 + q + 3) * 6 + i) * 256 + ct] = m;
          }
          __syncwarp();
          if (lane == 0) red_release(g_flags + (FL_A + sblk * 3 + q) * 32, 1u);
        }
      }
      if (ct == 0) { STAMP(4); g_epoch[cta * 32] = ep1; }
    }
  }
}

typedef CUresult (*EncFn)(CUtensorMap*, CUtensorMapDataType, cuuint32_t, void*, const cuuint64_t*, const cuuint64_t*, const cuuint32_t*,
                          const cuuint32_t*, CUtensorMapInterleave, CUtensorMapSwizzle, CUtensorMapL2promotion, CUtensorMapFloatOOBfill);

void mk2d(EncFn enc, CUtensorMap* m, const void* p, uint64_t inner, uint64_t outer, uint32_t bi, uint32_t bo, CUtensorMapSwizzle sw) {
  cuuint64_t dims[2] = {inner, outer}; cuuint64_t str[1] = {inner * 2}; cuuint32_t box[2] = {bi, bo}; cuuint32_t es[2] = {1, 1};
  enc(m, CU_TENSOR_MAP_DATA_TYPE_BFLOAT16, 2, const_cast<void*>(p), dims, str, box, es, CU_TENSOR_MAP_INTERLEAVE_NONE, sw,
      CU_TENSOR_MAP_L2_PROMOTION_L2_256B, CU_TENSOR_MAP_FLOAT_OOB_FILL_NONE);
}
void mk3d(EncFn enc, CUtensorMap* m, const void* p) {
  cuuint64_t dims[3] = {64, 32, 576}; cuuint64_t str[2] = {128, 4096}; cuuint32_t box[3] = {64, 32, 2}; cuuint32_t es[3] = {1, 1, 1};
  enc(m, CU_TENSOR_MAP_DATA_TYPE_BFLOAT16, 3, const_cast<void*>(p), dims, str, box, es, CU_TENSOR_MAP_INTERLEAVE_NONE, CU_TENSOR_MAP_SWIZZLE_128B,
      CU_TENSOR_MAP_L2_PROMOTION_L2_256B, CU_TENSOR_MAP_FLOAT_OOB_FILL_NONE);
}

}

extern "C" void kernel_launch(void* const* d_in, const int* in_sizes, int n_in, void* d_out, int out_size) {
  (void)in_sizes; (void)n_in; (void)out_size;
  static EncFn enc = nullptr;
  static void *p_h, *p_u, *p_xb, *p_TF, *p_X1T, *p_ZT;
  if (!enc) {
    void* fn = nullptr;
    cudaDriverEntryPointQueryResult qr;
    cudaGetDriverEntryPoint("cuTensorMapEncodeTiled", &fn, cudaEnableDefault, &qr);
    enc = (EncFn)fn;
    cudaFuncSetAttribute(mega_kernel, cudaFuncAttributeMaxDynamicSharedMemorySize, SM_TOTAL);
    cudaGetSymbolAddress(&p_h, g_h); cudaGetSymbolAddress(&p_u, g_u); cudaGetSymbolAddress(&p_xb, g_xb);
    cudaGetSymbolAddress(&p_TF, g_TF); cudaGetSymbolAddress(&p_X1T, g_X1T); cudaGetSymbolAddress(&p_ZT, g_ZT);
  }
  Params P;
  const CUtensorMapSwizzle S128 = CU_TENSOR_MAP_SWIZZLE_128B;
  mk2d(enc, &P.tW1, d_in[4], F_, S_, 64, 64, S128);
  mk2d(enc, &P.tH, p_h, D_, S_, 64, 64, S128);
  mk2d(enc, &P.tW2, d_in[6], S_, F_, 64, 64, S128);
  mk2d(enc, &P.tU, p_u, D_, F_, 64, 64, S128);
  mk2d(enc, &P.tOut, d_out, D_, S_, 32, 64, CU_TENSOR_MAP_SWIZZLE_64B);
  mk2d(enc, &P.tXB, p_xb, D_, S_, 64, 128, S128);
  mk2d(enc, &P.tTFk, p_TF, 288, 576, 64, 96, S128);
  mk2d(enc, &P.tX1s, p_X1T, S_, 576, 64, 96, S128);
  mk3d(enc, &P.tX1c, p_X1T);
  mk3d(enc, &P.tZc, p_ZT);
  mk2d(enc, &P.tZT, p_ZT, S_, 576, 64, 64, S128);
  mk2d(enc, &P.tTFn, p_TF, 288, 576, 64, 64, S128);
  P.Ax = (const bf16*)d_in[0]; P.Wr = (const bf16*)d_in[1]; P.Wi = (const bf16*)d_in[2];
  P.b1 = (const bf16*)d_in[5]; P.b2 = (const bf16*)d_in[7]; P.gw = (const bf16*)d_in[8];

  cudaLaunchConfig_t cfg = {};
  cfg.gridDim = dim3(NCTA); cfg.blockDim = dim3(NTHREADS); cfg.dynamicSmemBytes = SM_TOTAL; cfg.stream = cudaStreamPerThread;
  cudaLaunchAttribute at[1];
  at[0].id = cudaLaunchAttributeClusterDimension; at[0].val.clusterDim.x = 2; at[0].val.clusterDim.y = 1; at[0].val.clusterDim.z = 1;
  cfg.attrs = at; cfg.numAttrs = 1;
  cudaLaunchKernelEx(&cfg, mega_kernel, P);
}
```

```cpp
#include <cuda_runtime.h>
#include <cuda_bf16.h>
#include <cuda.h>
#include <stdint.h>

template<int TA, int TB> __device__ __forceinline__ void wg_ss_n192(float (&d)[96], uint64_t da, uint64_t db, int sd) {
  asm volatile("{\n.reg .pred p;\nsetp.ne.b32 p, %98, 0;\n"
    "wgmma.mma_async.sync.aligned.m64n192k16.f32.bf16.bf16 {%0, %1, %2, %3, %4, %5, %6, %7, %8, %9, %10, %11, %12, %13, %14, %15, %16, %17, %18, %19, %20, %21, %22, %23, %24, %25, %26, %27, %28, %29, %30, %31, %32, %33, %34, %35, %36, %37, %38, %39, %40, %41, %42, %43, %44, %45, %46, %47, %48, %49, %50, %51, %52, %53, %54, %55, %56, %57, %58, %59, %60, %61, %62, %63, %64, %65, %66, %67, %68, %69, %70, %71, %72, %73, %74, %75, %76, %77, %78, %79, %80, %81, %82, %83, %84, %85, %86, %87, %88, %89, %90, %91, %92, %93, %94, %95}, %96, %97, p, 1, 1, %99, %100;\n}\n"
    : "+f"(d[0]), "+f"(d[1]), "+f"(d[2]), "+f"(d[3]), "+f"(d[4]), "+f"(d[5]), "+f"(d[6]), "+f"(d[7]), "+f"(d[8]), "+f"(d[9]), "+f"(d[10]), "+f"(d[11]), "+f"(d[12]), "+f"(d[13]), "+f"(d[14]), "+f"(d[15]), "+f"(d[16]), "+f"(d[17]), "+f"(d[18]), "+f"(d[19]), "+f"(d[20]), "+f"(d[21]), "+f"(d[22]), "+f"(d[23]), "+f"(d[24]), "+f"(d[25]), "+f"(d[26]), "+f"(d[27]), "+f"(d[28]), "+f"(d[29]), "+f"(d[30]), "+f"(d[31]), "+f"(d[32]), "+f"(d[33]), "+f"(d[34]), "+f"(d[35]), "+f"(d[36]), "+f"(d[37]), "+f"(d[38]), "+f"(d[39]), "+f"(d[40]), "+f"(d[41]), "+f"(d[42]), "+f"(d[43]), "+f"(d[44]), "+f"(d[45]), "+f"(d[46]), "+f"(d[47]), "+f"(d[48]), "+f"(d[49]), "+f"(d[50]), "+f"(d[51]), "+f"(d[52]), "+f"(d[53]), "+f"(d[54]), "+f"(d[55]), "+f"(d[56]), "+f"(d[57]), "+f"(d[58]), "+f"(d[59]), "+f"(d[60]), "+f"(d[61]), "+f"(d[62]), "+f"(d[63]), "+f"(d[64]), "+f"(d[65]), "+f"(d[66]), "+f"(d[67]), "+f"(d[68]), "+f"(d[69]), "+f"(d[70]), "+f"(d[71]), "+f"(d[72]), "+f"(d[73]), "+f"(d[74]), "+f"(d[75]), "+f"(d[76]), "+f"(d[77]), "+f"(d[78]), "+f"(d[79]), "+f"(d[80]), "+f"(d[81]), "+f"(d[82]), "+f"(d[83]), "+f"(d[84]), "+f"(d[85]), "+f"(d[86]), "+f"(d[87]), "+f"(d[88]), "+f"(d[89]), "+f"(d[90]), "+f"(d[91]), "+f"(d[92]), "+f"(d[93]), "+f"(d[94]), "+f"(d[95])
    : "l"(da), "l"(db), "r"(sd), "n"(TA), "n"(TB));
}

template<int TA, int TB> __device__ __forceinline__ void wg_ss_n144(float (&d)[72], uint64_t da, uint64_t db, int sd) {
  asm volatile("{\n.reg .pred p;\nsetp.ne.b32 p, %74, 0;\n"
    "wgmma.mma_async.sync.aligned.m64n144k16.f32.bf16.bf16 {%0, %1, %2, %3, %4, %5, %6, %7, %8, %9, %10, %11, %12, %13, %14, %15, %16, %17, %18, %19, %20, %21, %22, %23, %24, %25, %26, %27, %28, %29, %30, %31, %32, %33, %34, %35, %36, %37, %38, %39, %40, %41, %42, %43, %44, %45, %46, %47, %48, %49, %50, %51, %52, %53, %54, %55, %56, %57, %58, %59, %60, %61, %62, %63, %64, %65, %66, %67, %68, %69, %70, %71}, %72, %73, p, 1, 1, %75, %76;\n}\n"
    : "+f"(d[0]), "+f"(d[1]), "+f"(d[2]), "+f"(d[3]), "+f"(d[4]), "+f"(d[5]), "+f"(d[6]), "+f"(d[7]), "+f"(d[8]), "+f"(d[9]), "+f"(d[10]), "+f"(d[11]), "+f"(d[12]), "+f"(d[13]), "+f"(d[14]), "+f"(d[15]), "+f"(d[16]), "+f"(d[17]), "+f"(d[18]), "+f"(d[19]), "+f"(d[20]), "+f"(d[21]), "+f"(d[22]), "+f"(d[23]), "+f"(d[24]), "+f"(d[25]), "+f"(d[26]), "+f"(d[27]), "+f"(d[28]), "+f"(d[29]), "+f"(d[30]), "+f"(d[31]), "+f"(d[32]), "+f"(d[33]), "+f"(d[34]), "+f"(d[35]), "+f"(d[36]), "+f"(d[37]), "+f"(d[38]), "+f"(d[39]), "+f"(d[40]), "+f"(d[41]), "+f"(d[42]), "+f"(d[43]), "+f"(d[44]), "+f"(d[45]), "+f"(d[46]), "+f"(d[47]), "+f"(d[48]), "+f"(d[49]), "+f"(d[50]), "+f"(d[51]), "+f"(d[52]), "+f"(d[53]), "+f"(d[54]), "+f"(d[55]), "+f"(d[56]), "+f"(d[57]), "+f"(d[58]), "+f"(d[59]), "+f"(d[60]), "+f"(d[61]), "+f"(d[62]), "+f"(d[63]), "+f"(d[64]), "+f"(d[65]), "+f"(d[66]), "+f"(d[67]), "+f"(d[68]), "+f"(d[69]), "+f"(d[70]), "+f"(d[71])
    : "l"(da), "l"(db), "r"(sd), "n"(TA), "n"(TB));
}

template<int TA, int TB> __device__ __forceinline__ void wg_ss_n96(float (&d)[48], uint64_t da, uint64_t db, int sd) {
  asm volatile("{\n.reg .pred p;\nsetp.ne.b32 p, %50, 0;\n"
    "wgmma.mma_async.sync.aligned.m64n96k16.f32.bf16.bf16 {%0, %1, %2, %3, %4, %5, %6, %7, %8, %9, %10, %11, %12, %13, %14, %15, %16, %17, %18, %19, %20, %21, %22, %23, %24, %25, %26, %27, %28, %29, %30, %31, %32, %33, %34, %35, %36, %37, %38, %39, %40, %41, %42, %43, %44, %45, %46, %47}, %48, %49, p, 1, 1, %51, %52;\n}\n"
    : "+f"(d[0]), "+f"(d[1]), "+f"(d[2]), "+f"(d[3]), "+f"(d[4]), "+f"(d[5]), "+f"(d[6]), "+f"(d[7]), "+f"(d[8]), "+f"(d[9]), "+f"(d[10]), "+f"(d[11]), "+f"(d[12]), "+f"(d[13]), "+f"(d[14]), "+f"(d[15]), "+f"(d[16]), "+f"(d[17]), "+f"(d[18]), "+f"(d[19]), "+f"(d[20]), "+f"(d[21]), "+f"(d[22]), "+f"(d[23]), "+f"(d[24]), "+f"(d[25]), "+f"(d[26]), "+f"(d[27]), "+f"(d[28]), "+f"(d[29]), "+f"(d[30]), "+f"(d[31]), "+f"(d[32]), "+f"(d[33]), "+f"(d[34]), "+f"(d[35]), "+f"(d[36]), "+f"(d[37]), "+f"(d[38]), "+f"(d[39]), "+f"(d[40]), "+f"(d[41]), "+f"(d[42]), "+f"(d[43]), "+f"(d[44]), "+f"(d[45]), "+f"(d[46]), "+f"(d[47])
    : "l"(da), "l"(db), "r"(sd), "n"(TA), "n"(TB));
}

template<int TB> __device__ __forceinline__ void wg_rs_n64(float (&d)[32], uint32_t a0, uint32_t a1, uint32_t a2, uint32_t a3, uint64_t db, int sd) {
  asm volatile("{\n.reg .pred p;\nsetp.ne.b32 p, %37, 0;\n"
    "wgmma.mma_async.sync.aligned.m64n64k16.f32.bf16.bf16 {%0, %1, %2, %3, %4, %5, %6, %7, %8, %9, %10, %11, %12, %13, %14, %15, %16, %17, %18, %19, %20, %21, %22, %23, %24, %25, %26, %27, %28, %29, %30, %31}, {%32, %33, %34, %35}, %36, p, 1, 1, %38;\n}\n"
    : "+f"(d[0]), "+f"(d[1]), "+f"(d[2]), "+f"(d[3]), "+f"(d[4]), "+f"(d[5]), "+f"(d[6]), "+f"(d[7]), "+f"(d[8]), "+f"(d[9]), "+f"(d[10]), "+f"(d[11]), "+f"(d[12]), "+f"(d[13]), "+f"(d[14]), "+f"(d[15]), "+f"(d[16]), "+f"(d[17]), "+f"(d[18]), "+f"(d[19]), "+f"(d[20]), "+f"(d[21]), "+f"(d[22]), "+f"(d[23]), "+f"(d[24]), "+f"(d[25]), "+f"(d[26]), "+f"(d[27]), "+f"(d[28]), "+f"(d[29]), "+f"(d[30]), "+f"(d[31])
    : "r"(a0), "r"(a1), "r"(a2), "r"(a3), "l"(db), "r"(sd), "n"(TB));
}

template<int TB> __device__ __forceinline__ void wg_rs_n128(float (&d)[64], uint32_t a0, uint32_t a1, uint32_t a2, uint32_t a3, uint64_t db, int sd) {
  asm volatile("{\n.reg .pred p;\nsetp.ne.b32 p, %69, 0;\n"
    "wgmma.mma_async.sync.aligned.m64n128k16.f32.bf16.bf16 {%0, %1, %2, %3, %4, %5, %6, %7, %8, %9, %10, %11, %12, %13, %14, %15, %16, %17, %18, %19, %20, %21, %22, %23, %24, %25, %26, %27, %28, %29, %30, %31, %32, %33, %34, %35, %36, %37, %38, %39, %40, %41, %42, %43, %44, %45, %46, %47, %48, %49, %50, %51, %52, %53, %54, %55, %56, %57, %58, %59, %60, %61, %62, %63}, {%64, %65, %66, %67}, %68, p, 1, 1, %70;\n}\n"
    : "+f"(d[0]), "+f"(d[1]), "+f"(d[2]), "+f"(d[3]), "+f"(d[4]), "+f"(d[5]), "+f"(d[6]), "+f"(d[7]), "+f"(d[8]), "+f"(d[9]), "+f"(d[10]), "+f"(d[11]), "+f"(d[12]), "+f"(d[13]), "+f"(d[14]), "+f"(d[15]), "+f"(d[16]), "+f"(d[17]), "+f"(d[18]), "+f"(d[19]), "+f"(d[20]), "+f"(d[21]), "+f"(d[22]), "+f"(d[23]), "+f"(d[24]), "+f"(d[25]), "+f"(d[26]), "+f"(d[27]), "+f"(d[28]), "+f"(d[29]), "+f"(d[30]), "+f"(d[31]), "+f"(d[32]), "+f"(d[33]), "+f"(d[34]), "+f"(d[35]), "+f"(d[36]), "+f"(d[37]), "+f"(d[38]), "+f"(d[39]), "+f"(d[40]), "+f"(d[41]), "+f"(d[42]), "+f"(d[43]), "+f"(d[44]), "+f"(d[45]), "+f"(d[46]), "+f"(d[47]), "+f"(d[48]), "+f"(d[49]), "+f"(d[50]), "+f"(d[51]), "+f"(d[52]), "+f"(d[53]), "+f"(d[54]), "+f"(d[55]), "+f"(d[56]), "+f"(d[57]), "+f"(d[58]), "+f"(d[59]), "+f"(d[60]), "+f"(d[61]), "+f"(d[62]), "+f"(d[63])
    : "r"(a0), "r"(a1), "r"(a2), "r"(a3), "l"(db), "r"(sd), "n"(TB));
}

namespace {

typedef __nv_bfloat16 bf16;

constexpr int S_ = 2048, D_ = 576, F_ = 4608, DF_ = 289;
constexpr int NCTA = 132, NG = 108, NTHREADS = 384;

constexpr uint32_t STAGE_BYTES = 40960;
constexpr uint32_t SM_STG = 163840;
constexpr uint32_t SM_SIDE = 212992;
constexpr uint32_t SM_BAR = 231680;
constexpr uint32_t SM_TOTAL = 232448;
constexpr uint32_t B_FULL = SM_BAR  , B_EMPTY = SM_BAR + 64  , B_X = SM_BAR + 128, B_PFREE = SM_BAR + 136, B_LFREE = SM_BAR + 144,
                   B_W = SM_BAR + 152, B_AUX = SM_BAR + 160, B_F2 = SM_BAR + 168  , B_F2DONE = SM_BAR + 200, B_RES3 = SM_BAR + 208,
                   B3_FULL = SM_BAR + 216  , B3_EMPTY = SM_BAR + 272  , B_XR = SM_BAR + 328;
constexpr uint32_t F1_RING = 92160;
constexpr uint32_t F1_STG = 190464;
constexpr uint32_t F_C64 = 147456;
constexpr uint32_t F_ATAB = 163840;
constexpr uint32_t F_LUT = 180224;
constexpr uint32_t F3_RING = 110592;

constexpr int FL_H = 0, FL_U = 32, FL_XB = 140, FL_TI = 156, FL_WT = 157, FL_X1 = 158, FL_Z = 159, FL_A = 160, NFLAGS = 208;

struct Params {
  const bf16 *Ax, *gw;
  bf16 *h, *xb;
  unsigned *flags, *epoch;
  float* gate;
  const bf16 *Wr, *Wi, *b1, *b2;
  uint32_t* Wt;
  uint2* W0;
  bf16* TI;
  uint4* afrag;
  long long* stamp;
  CUtensorMap tW1, tH, tW2, tU, tOut, tXB, tTI, tX1s, tX1c, tZc, tZT;
};

}

__device__ __align__(1024) bf16 g_h[S_ * D_];
__device__ __align__(1024) bf16 g_u[F_ * D_];
__device__ __align__(1024) bf16 g_xb[2 * S_ * 320];
__device__ __align__(1024) bf16 g_TI[288 * 576];
__device__ __align__(1024) bf16 g_X1T[576 * S_];
__device__ __align__(1024) bf16 g_ZT[576 * S_];
__device__ __align__(1024) uint32_t g_Wt[288 * 2048];
__device__ __align__(1024) uint4 g_afrag[16 * 6 * 6 * 256];
__device__ __align__(1024) uint2 g_W0[2048];
__device__ __align__(1024) float g_gate[S_];
__device__ __align__(1024) unsigned g_flags[NFLAGS * 32];
__device__ __align__(1024) unsigned g_epoch[NCTA * 32];

#define STAMP(i) do { } while (0)

namespace {

#define XDLY0 900
#define XDLY1 10
#define W1T1 2000
#define W1DT 800
#define W2PF 0
constexpr long long TIMEOUT_CYC = 400000000LL;

__device__ __forceinline__ bool on_timeout(int site) {
  __trap();
  return true;
}
__device__ __forceinline__ bool aborted() {
  return false;
}

__device__ __forceinline__ uint32_t smem_u32(const void* p) { return (uint32_t)__cvta_generic_to_shared(p); }
__device__ __forceinline__ void mbar_init(uint32_t bar, uint32_t cnt) { asm volatile("mbarrier.init.shared::cta.b64 [%0], %1;" ::"r"(bar), "r"(cnt) : "memory"); }
__device__ __forceinline__ void mbar_expect_tx(uint32_t bar, uint32_t bytes) { asm volatile("mbarrier.arrive.expect_tx.shared::cta.b64 _, [%0], %1;" ::"r"(bar), "r"(bytes) : "memory"); }
__device__ __forceinline__ void mbar_arrive(uint32_t bar) { asm volatile("mbarrier.arrive.shared::cta.b64 _, [%0];" ::"r"(bar) : "memory"); }
__device__ __forceinline__ uint32_t mapa(uint32_t addr, uint32_t cta) {
  uint32_t r; asm("mapa.shared::cluster.u32 %0, %1, %2;" : "=r"(r) : "r"(addr), "r"(cta)); return r;
}
__device__ __forceinline__ void mbar_arrive_remote(uint32_t raddr) { asm volatile("mbarrier.arrive.release.cluster.shared::cluster.b64 _, [%0];" ::"r"(raddr) : "memory"); }
__device__ __forceinline__ bool mbar_try(uint32_t bar, uint32_t parity) {
  uint32_t ok;
  asm volatile("{\n.reg .pred p;\nmbarrier.try_wait.parity.shared::cta.b64 p, [%1], %2;\nselp.u32 %0, 1, 0, p;\n}" : "=r"(ok) : "r"(bar), "r"(parity) : "memory");
  return ok != 0;
}
__device__ __forceinline__ bool mbar_try_cl(uint32_t bar, uint32_t parity) {
  uint32_t ok;
  asm volatile("{\n.reg .pred p;\nmbarrier.try_wait.parity.acquire.cluster.shared::cta.b64 p, [%1], %2;\nselp.u32 %0, 1, 0, p;\n}" : "=r"(ok) : "r"(bar), "r"(parity) : "memory");
  return ok != 0;
}
__device__ __forceinline__ void mbar_wait(uint32_t bar, uint32_t parity, int) {
  asm volatile("{\n.reg .pred p;\n.reg .u32 c;\nmov.u32 c, 0;\n"
               "LW: mbarrier.try_wait.parity.shared::cta.b64 p, [%0], %1;\n@p bra LD;\n"
               "add.u32 c, c, 1;\nsetp.lt.u32 p, c, 0x400000;\n@p bra LW;\ntrap;\nLD:\n}" ::"r"(bar), "r"(parity) : "memory");
}
__device__ __forceinline__ void mbar_wait_cl(uint32_t bar, uint32_t parity, int) {
  asm volatile("{\n.reg .pred p;\n.reg .u32 c;\nmov.u32 c, 0;\n"
               "LW: mbarrier.try_wait.parity.acquire.cluster.shared::cta.b64 p, [%0], %1;\n@p bra LD;\n"
               "add.u32 c, c, 1;\nsetp.lt.u32 p, c, 0x400000;\n@p bra LW;\ntrap;\nLD:\n}" ::"r"(bar), "r"(parity) : "memory");
}
__device__ __forceinline__ unsigned ld_acquire(const unsigned* p) {
  unsigned v; asm volatile("ld.acquire.gpu.global.u32 %0, [%1];" : "=r"(v) : "l"(p) : "memory"); return v;
}
__device__ __forceinline__ void red_release(unsigned* p, unsigned v) { asm volatile("red.release.gpu.global.add.u32 [%0], %1;" ::"l"(p), "r"(v) : "memory"); }
__device__ __forceinline__ void fence_async_glb() { asm volatile("fence.proxy.async.global;" ::: "memory"); }
__device__ __forceinline__ void fence_async_smem() { asm volatile("fence.proxy.async.shared::cta;" ::: "memory"); }
__device__ __forceinline__ unsigned ld_epoch_raw(const unsigned* epoch, int cta) {
  unsigned v; asm volatile("ld.relaxed.gpu.global.u32 %0, [%1];" : "=r"(v) : "l"(epoch + cta * 32) : "memory"); return v;
}
__device__ __forceinline__ unsigned ld_epoch(const unsigned* epoch, int cta) { return ld_epoch_raw(epoch, cta) + 1; }
__device__ __forceinline__ void red_relaxed(unsigned* p, unsigned v) { asm volatile("red.relaxed.gpu.global.add.u32 [%0], %1;" ::"l"(p), "r"(v) : "memory"); }
__device__ __forceinline__ void fence_gpu() { asm volatile("fence.acq_rel.gpu;" ::: "memory"); }
__device__ __forceinline__ void wait_flag(const unsigned* flags, int idx, unsigned target, int site) {
  const unsigned* p = flags + idx * 32;
  asm volatile("{\n.reg .pred p;\n.reg .u32 c, v;\nmov.u32 c, 0;\n"
               "LW: ld.acquire.gpu.global.u32 v, [%0];\nsub.u32 v, v, %1;\nsetp.ge.s32 p, v, 0;\n@p bra LD;\n"
               "add.u32 c, c, 1;\nsetp.lt.u32 p, c, 0x200000;\n@p bra LW;\ntrap;\nLD:\n}" ::"l"(p), "r"(target) : "memory");
}
__device__ __forceinline__ uint32_t poll_mask(const unsigned* flags, int idx0, int n, unsigned target, int need, int site) {
  const int lane = threadIdx.x & 31;
  const unsigned* p = flags + (idx0 + (lane < n ? lane : 0)) * 32;
  uint32_t m;
#pragma unroll 1
  for (uint32_t it = 0;; it++) {
    unsigned v = ld_acquire(p);
    m = __ballot_sync(0xffffffffu, (int)(v - target) >= 0);
    if ((m >> need) & 1) break;
    if (it > 0x200000u) __trap();
  }
  fence_async_glb();
  return m;
}

__device__ __forceinline__ void tma2d(uint32_t dst, const CUtensorMap* m, int c0, int c1, uint32_t bar) {
  asm volatile("cp.async.bulk.tensor.2d.shared::cluster.global.mbarrier::complete_tx::bytes [%0], [%1, {%3, %4}], [%2];"
               ::"r"(dst), "l"(m), "r"(bar), "r"(c0), "r"(c1) : "memory");
}
__device__ __forceinline__ void tma2d_pf(const CUtensorMap* m, int c0, int c1) {
  asm volatile("cp.async.bulk.prefetch.tensor.2d.L2.global [%0, {%1, %2}];" ::"l"(m), "r"(c0), "r"(c1) : "memory");
}
__device__ __forceinline__ void tma3d(uint32_t dst, const CUtensorMap* m, int c0, int c1, int c2, uint32_t bar) {
  asm volatile("cp.async.bulk.tensor.3d.shared::cluster.global.mbarrier::complete_tx::bytes [%0], [%1, {%3, %4, %5}], [%2];"
               ::"r"(dst), "l"(m), "r"(bar), "r"(c0), "r"(c1), "r"(c2) : "memory");
}
__device__ __forceinline__ void tma2d_st(const CUtensorMap* m, uint32_t src, int c0, int c1) {
  asm volatile("cp.async.bulk.tensor.2d.global.shared::cta.bulk_group [%0, {%2, %3}], [%1];" ::"l"(m), "r"(src), "r"(c0), "r"(c1) : "memory");
}
__device__ __forceinline__ void tma3d_st(const CUtensorMap* m, uint32_t src, int c0, int c1, int c2) {
  asm volatile("cp.async.bulk.tensor.3d.global.shared::cta.bulk_group [%0, {%2, %3, %4}], [%1];" ::"l"(m), "r"(src), "r"(c0), "r"(c1), "r"(c2) : "memory");
}
__device__ __forceinline__ void bulk_ld(uint32_t dst, const void* src, uint32_t bytes, uint32_t bar) {
  asm volatile("cp.async.bulk.shared::cluster.global.mbarrier::complete_tx::bytes [%0], [%1], %2, [%3];" ::"r"(dst), "l"(src), "r"(bytes), "r"(bar) : "memory");
}
__device__ __forceinline__ void bulk_commit() { asm volatile("cp.async.bulk.commit_group;" ::: "memory"); }
__device__ __forceinline__ void bulk_wait0() { asm volatile("cp.async.bulk.wait_group 0;" ::: "memory"); }
__device__ __forceinline__ void bulk_wait0_read() { asm volatile("cp.async.bulk.wait_group.read 0;" ::: "memory"); }
__device__ __forceinline__ void prefetch_map(const CUtensorMap* m) { asm volatile("prefetch.tensormap [%0];" ::"l"(m) : "memory"); }

__device__ __forceinline__ uint64_t mkdesc(uint32_t addr, uint32_t lbo, uint32_t sbo) {
  return (uint64_t)((addr & 0x3FFFF) >> 4) | ((uint64_t)(lbo >> 4) << 16) | ((uint64_t)(sbo >> 4) << 32) | (1ull << 62);
}
__device__ __forceinline__ void wg_fence() { asm volatile("wgmma.fence.sync.aligned;" ::: "memory"); }
__device__ __forceinline__ void wg_commit() { asm volatile("wgmma.commit_group.sync.aligned;" ::: "memory"); }
template <int N> __device__ __forceinline__ void wg_wait() { asm volatile("wgmma.wait_group.sync.aligned %0;" ::"n"(N) : "memory"); }
__device__ __forceinline__ void bar_sync(int id, int n) { asm volatile("bar.sync %0, %1;" ::"r"(id), "r"(n) : "memory"); }

__device__ __forceinline__ uint32_t pack2(float lo, float hi) {
  uint32_t r; asm("cvt.rn.bf16x2.f32 %0, %1, %2;" : "=r"(r) : "f"(hi), "f"(lo)); return r;
}
__device__ __forceinline__ float bf_lo(uint32_t v) { return __uint_as_float(v << 16); }
__device__ __forceinline__ float bf_hi(uint32_t v) { return __uint_as_float(v & 0xffff0000u); }
__device__ __forceinline__ float bfr(float x) { return bf_lo(pack2(x, 0.f)); }
__device__ __forceinline__ uint32_t badd2(uint32_t a, uint32_t b) { uint32_t r; asm("add.rn.bf16x2 %0, %1, %2;" : "=r"(r) : "r"(a), "r"(b)); return r; }
__device__ __forceinline__ uint32_t bsub2(uint32_t a, uint32_t b) { uint32_t r; asm("sub.rn.bf16x2 %0, %1, %2;" : "=r"(r) : "r"(a), "r"(b)); return r; }
__device__ __forceinline__ uint32_t bmul2(uint32_t a, uint32_t b) { uint32_t r; asm("mul.rn.bf16x2 %0, %1, %2;" : "=r"(r) : "r"(a), "r"(b)); return r; }
__device__ __forceinline__ uint32_t dup_bf(const bf16* p) { uint32_t v = *reinterpret_cast<const uint16_t*>(p); return v | (v << 16); }
__device__ __forceinline__ float cos_frac(int m, int n) { return __cosf((float)(2 * m > n ? m - n : m) * (6.283185307179586f / (float)n)); }
__device__ __forceinline__ float sin_frac(int m, int n) { return __sinf((float)(2 * m > n ? m - n : m) * (6.283185307179586f / (float)n)); }
__device__ __forceinline__ void stsm4(uint32_t addr, uint32_t a, uint32_t b, uint32_t c, uint32_t d) {
  asm volatile("stmatrix.sync.aligned.m8n8.x4.shared.b16 [%0], {%1, %2, %3, %4};" ::"r"(addr), "r"(a), "r"(b), "r"(c), "r"(d) : "memory");
}
__device__ __forceinline__ void stsm4t(uint32_t addr, uint32_t a, uint32_t b, uint32_t c, uint32_t d) {
  asm volatile("stmatrix.sync.aligned.m8n8.x4.trans.shared.b16 [%0], {%1, %2, %3, %4};" ::"r"(addr), "r"(a), "r"(b), "r"(c), "r"(d) : "memory");
}
__device__ __forceinline__ float gelu_tanh(float x) {
  float x2 = x * x;
  float z = x * fmaf(x2, 0.044715f * 0.7978845608028654f, 0.7978845608028654f);
  float t; asm("tanh.approx.f32 %0, %1;" : "=f"(t) : "f"(z));
  float hx = 0.5f * x;
  return fmaf(hx, t, hx);
}

__device__ __forceinline__ void bar_arrive(int id, int n) { asm volatile("bar.arrive %0, %1;" ::"r"(id), "r"(n) : "memory"); }
__device__ __forceinline__ void pair_load(uint32_t src, int lane, uint32_t (&lo)[2][5], uint32_t (&hi)[2][5]) {
#pragma unroll
  for (int r = 0; r < 2; r++)
#pragma unroll
    for (int i = 0; i < 5; i++) {
      lo[r][i] = 0u; hi[r][i] = 0u;
      if (i < 4 || lane < 16) {
        asm volatile("ld.shared.u32 %0, [%1];" : "=r"(lo[r][i]) : "r"(src + r * 1152 + lane * 4 + i * 128) : "memory");
        asm volatile("ld.shared.u32 %0, [%1];" : "=r"(hi[r][i]) : "r"(src + r * 1152 + 576 + lane * 4 + i * 128) : "memory");
      }
    }
}
__device__ __forceinline__ void ln_pair(const Params& P, int row, int lane, const uint32_t (&lo)[2][5], const uint32_t (&hi)[2][5]) {
  const bool ok4 = lane < 16;
  float c[2], s[2], q[2];
#pragma unroll
  for (int r = 0; r < 2; r++) c[r] = __shfl_sync(0xffffffffu, bf_lo(lo[r][0]), 0);
#pragma unroll
  for (int r = 0; r < 2; r++) {
    float s0 = 0.f, s1 = 0.f, q0 = 0.f, q1 = 0.f;
#pragma unroll
    for (int i = 0; i < 5; i++) {
      float d0 = bf_lo(lo[r][i]) - c[r], d1 = bf_hi(lo[r][i]) - c[r], d2 = bf_lo(hi[r][i]) - c[r], d3 = bf_hi(hi[r][i]) - c[r];
      if (i == 4 && !ok4) { d0 = 0.f; d1 = 0.f; d2 = 0.f; d3 = 0.f; }
      s0 += d0 + d1; s1 += d2 + d3;
      q0 = fmaf(d0, d0, fmaf(d1, d1, q0)); q1 = fmaf(d2, d2, fmaf(d3, d3, q1));
    }
    s[r] = s0 + s1; q[r] = q0 + q1;
  }
#pragma unroll
  for (int o = 16; o > 0; o >>= 1) {
#pragma unroll
    for (int r = 0; r < 2; r++) { s[r] += __shfl_xor_sync(0xffffffffu, s[r], o); q[r] += __shfl_xor_sync(0xffffffffu, q[r], o); }
  }
#pragma unroll
  for (int r = 0; r < 2; r++) {
    const float m = s[r] * (1.0f / 576.0f);
    const float var = fmaxf(fmaf(q[r], 1.0f / 576.0f, -m * m), 0.f);
    const uint32_t mb = pack2(m + c[r], m + c[r]);
    float sq, rs;
    asm("sqrt.approx.f32 %0, %1;" : "=f"(sq) : "f"(bfr(bfr(var) + 1e-5f)));
    asm("rcp.approx.f32 %0, %1;" : "=f"(rs) : "f"(bfr(sq)));
    uint32_t* h = reinterpret_cast<uint32_t*>(P.h + (size_t)(row + r) * D_) + lane;
#pragma unroll
    for (int i = 0; i < 5; i++) {
      const uint32_t d0 = bsub2(lo[r][i], mb), d1 = bsub2(hi[r][i], mb);
      if (i < 4 || ok4) {
        h[32 * i] = pack2(bf_lo(d0) * rs, bf_hi(d0) * rs);
        h[144 + 32 * i] = pack2(bf_lo(d1) * rs, bf_hi(d1) * rs);
      }
    }
  }
}
__device__ __forceinline__ void xb_pair(const Params& P, int row, int lane, const uint32_t (&lo)[2][5], const uint32_t (&hi)[2][5],
                                        const uint32_t (&gl)[5], const uint32_t (&gh)[5]) {
  float z[2] = {0.f, 0.f};
#pragma unroll
  for (int r = 0; r < 2; r++) {
    uint32_t* xb = reinterpret_cast<uint32_t*>(P.xb + (size_t)(row + r) * 320) + lane;
#pragma unroll
    for (int i = 0; i < 5; i++) {
      if (i < 4 || lane < 16) {
        xb[32 * i] = badd2(lo[r][i], hi[r][i]);
        xb[S_ * 160 + 32 * i] = bsub2(lo[r][i], hi[r][i]);
      }
      const uint32_t p0 = bmul2(lo[r][i], gl[i]), p1 = bmul2(hi[r][i], gh[i]);
      z[r] += (bf_lo(p0) + bf_hi(p0)) + (bf_lo(p1) + bf_hi(p1));
    }
  }
#pragma unroll
  for (int o = 16; o > 0; o >>= 1) { z[0] += __shfl_xor_sync(0xffffffffu, z[0], o); z[1] += __shfl_xor_sync(0xffffffffu, z[1], o); }
  if (lane < 2) P.gate[row + lane] = bfr(1.0f / (1.0f + __expf(-bfr(lane ? z[1] : z[0]))));
}

__device__ __forceinline__ void w_job(const Params& P, uint32_t sb, uint32_t base, int unit, int t3, int lane) {
  mbar_wait(sb + B_W, 0, 1);
  const int w = unit & 3, jp = unit >> 2;
#pragma unroll 2
  for (int it = 0; it < 12; it++) {
    int idx = t3 + 96 * it;
    int ip = idx & 3, cc = idx >> 2;
    int k = cc < 144 ? 2 * cc : 2 * (cc - 144) + 1;
    uint32_t o[4];
#pragma unroll
    for (int ii = 0; ii < 2; ii++) {
#pragma unroll
      for (int e = 0; e < 2; e++) {
        uint32_t off = base + e * 4624 + ((2 * ip + ii) * DF_ + k) * 2;
        uint16_t wr, wi;
        asm volatile("ld.shared.u16 %0, [%1];" : "=h"(wr) : "r"(off));
        asm volatile("ld.shared.u16 %0, [%1];" : "=h"(wi) : "r"(off + 9248));
        o[ii * 2 + e] = (uint32_t)wr | ((uint32_t)wi << 16);
      }
    }
    uint4* dst = reinterpret_cast<uint4*>(P.Wt + (size_t)cc * 2048 + (jp * 32 + 8 * w + 2 * ip) * 2);
    *dst = make_uint4(o[0], o[1], o[2], o[3]);
  }
  if (t3 < 16) {
    const uint32_t off = base + (t3 >> 3) * 4624 + (t3 & 7) * DF_ * 2;
    uint16_t a, b, c, d;
    asm volatile("ld.shared.u16 %0, [%1];" : "=h"(a) : "r"(off));
    asm volatile("ld.shared.u16 %0, [%1];" : "=h"(b) : "r"(off + 9248));
    asm volatile("ld.shared.u16 %0, [%1];" : "=h"(c) : "r"(off + 576));
    asm volatile("ld.shared.u16 %0, [%1];" : "=h"(d) : "r"(off + 9248 + 576));
    P.W0[64 * jp + 8 * w + (t3 & 7) + 32 * (t3 >> 3)] = make_uint2((uint32_t)a | ((uint32_t)b << 16), (uint32_t)c | ((uint32_t)d << 16));
  }
  __syncwarp();
  if (lane == 0) { mbar_arrive(sb + B_AUX); red_release(P.flags + FL_WT * 32, 1u); }
}

__device__ __forceinline__ void cs576(float m, float& c, float& s) {
  const float q = fmaf(m, 1.0f / 576.0f, 12582912.0f) - 12582912.0f;
  const float a = fmaf(q, -576.0f, m) * (6.283185307179586f / 576.0f);
  c = __cosf(a); s = __sinf(a);
}
__device__ __forceinline__ int col_freq(int cc) { return cc < 144 ? 2 * cc : 2 * (cc - 144) + 1; }

__device__ __forceinline__ void b1_gen(uint32_t sb, int nb, int cw, int lane) {
#pragma unroll 1
  for (int rp = cw; rp < 72; rp += 8) {
    const int cc = 72 * nb + rp;
    const float kf = (float)col_freq(cc);
    float cd, sd;
    cs576(kf, cd, sd);
    const uint32_t r0 = 2 * rp;
    uint32_t a0 = sb + r0 * 128 + (((lane >> 2) ^ (r0 & 7)) << 4) + (lane & 3) * 4;
    uint32_t a1 = sb + (r0 + 1) * 128 + (((lane >> 2) ^ ((r0 + 1) & 7)) << 4) + (lane & 3) * 4;
    float m = kf * (float)(2 * lane);
#pragma unroll
    for (int kb = 0; kb < 5; kb++) {
      float c0, s0;
      cs576(m, c0, s0);
      m = fmaf(kf, 64.0f, m);
      const float c1 = c0 * cd - s0 * sd, s1 = s0 * cd + c0 * sd;
      const uint32_t w1 = cc == 0 ? 0xBF803F80u : pack2(-s0, -s1);
      if (kb < 4 || lane < 16) {
        asm volatile("st.shared.u32 [%0], %1;" ::"r"(a0 + kb * 18432), "r"(pack2(c0, c1)) : "memory");
        asm volatile("st.shared.u32 [%0], %1;" ::"r"(a1 + kb * 18432), "r"(w1) : "memory");
      }
    }
  }
}

__device__ __forceinline__ uint32_t lut2(uint32_t lut, int i0, int i1) {
  uint16_t a, b;
  asm volatile("ld.shared.u16 %0, [%1];" : "=h"(a) : "r"(lut + (i0 & 63) * 2));
  asm volatile("ld.shared.u16 %0, [%1];" : "=h"(b) : "r"(lut + (i1 & 63) * 2));
  return (uint32_t)a | ((uint32_t)b << 16);
}
__device__ __forceinline__ void f2_consts(uint32_t sb, int t) {
  const uint32_t lut = sb + F_LUT;
  {
    const int n = t, g = n >> 3, qq = (n >> 1) & 3;
    const int pi = 16 * (g >> 2) + 8 * ((g >> 1) & 1) + 2 * qq + (g & 1);
    int a = (n & 1) * 48;
#pragma unroll 2
    for (int c = 0; c < 8; c++) {
      uint32_t w[4];
#pragma unroll
      for (int e = 0; e < 4; e++) { w[e] = lut2(lut, a, a + pi); a += 2 * pi; }
      asm volatile("st.shared.v4.b32 [%0], {%1, %2, %3, %4};" ::"r"(sb + F_C64 + n * 128 + ((c ^ (n & 7)) << 4)), "r"(w[0]), "r"(w[1]), "r"(w[2]), "r"(w[3]) : "memory");
    }
  }
  {
    const int wq = t >> 5, r8 = (t >> 2) & 7, q4 = t & 3;
#pragma unroll 2
    for (int tt = 0; tt < 4; tt++) {
      uint32_t f[4], v[4];
#pragma unroll
      for (int m = 0; m < 4; m++) {
        const int k0 = 16 * tt + 8 * (m >> 1) + 2 * q4, j1 = 8 * wq + r8;
        const int rip = m & 1, ri = tt >> 1;
        const int of = (rip == ri) ? 0 : (rip ? 8 : 24);
        f[m] = lut2(lut, 2 * (j1 * (k0 & 31) + of), 2 * (j1 * ((k0 + 1) & 31) + of));
        const int row = 16 * wq + 8 * (m & 1) + r8;
        const int rp2 = wq >> 1, ri2 = m >> 1;
        const int oi = (rp2 == ri2) ? 0 : (rp2 ? 24 : 8);
        const int jj = 8 * tt + 2 * q4;
        v[m] = lut2(lut, 2 * ((row & 31) * jj + oi), 2 * ((row & 31) * (jj + 1) + oi));
      }
      asm volatile("st.shared.v4.b32 [%0], {%1, %2, %3, %4};" ::"r"(sb + F_ATAB + tt * 2048 + t * 16), "r"(f[0]), "r"(f[1]), "r"(f[2]), "r"(f[3]) : "memory");
      asm volatile("st.shared.v4.b32 [%0], {%1, %2, %3, %4};" ::"r"(sb + F_ATAB + 8192 + tt * 2048 + t * 16), "r"(v[0]), "r"(v[1]), "r"(v[2]), "r"(v[3]) : "memory");
    }
  }
}

__device__ __forceinline__ void ti_gen(const Params& P, int fc, int t3, int lane) {
#pragma unroll 1
  for (int i = 0; i < 12; i++) {
    const int dr = 12 * fc + i;
#pragma unroll
    for (int b = 0; b < 3; b++) {
      const int cc = t3 + 96 * b;
      float c, s;
      cs576((float)(dr * col_freq(cc)), c, s);
      if (cc == 0) s = (dr & 1) ? 1.0f : -1.0f;
      reinterpret_cast<uint32_t*>(P.TI)[dr * 288 + cc] = pack2(c, -s);
    }
  }
  __syncwarp();
  if (lane == 0) red_release(P.flags + FL_TI * 32, 1u);
}

__device__ __forceinline__ int g2_f0(int i2, int gp, int rank) {
  const int n2 = i2 >> 1;
  const int tl = n2 == 0 ? gp : (n2 - 1 < gp ? n2 - 1 : n2);
  return (18 * rank + tl) * 128 + (i2 & 1) * 64;
}
__device__ __forceinline__ void w2_prefetch(const Params& P, int i2, int gp, int gj, int rank) {
  if (i2 % 3 == gj) {
    const int f0 = g2_f0(i2, gp, rank);
    tma2d_pf(&P.tW2, gp * 128, f0);
    tma2d_pf(&P.tW2, gp * 128 + 64, f0);
  }
}

__global__ void __launch_bounds__(NTHREADS, 1) mega_kernel(const __grid_constant__ Params P) {
  extern __shared__ __align__(1024) uint8_t smem_raw[];
  const uint32_t sb = smem_u32(smem_raw);
  const int tid = threadIdx.x, warp = tid >> 5, lane = tid & 31;
  const int cta = blockIdx.x;
  const uint32_t rank = cta & 1;
  const uint32_t c_start = (uint32_t)clock();
  const long long t_start = 0;
  const bool isG = cta < NG;
  const int row0 = ((cta + 20) & 127) * 16;
  const uint32_t side = sb + (isG ? SM_SIDE : F1_STG);
  if (tid == 0) {
    if (sb & 1023u) __trap();
    mbar_init(sb + B_XR, 1);
    if (!isG && cta < 128) {
      asm volatile("fence.mbarrier_init.release.cluster;" ::: "memory");
      mbar_expect_tx(sb + B_XR, 18432);
      bulk_ld(side, P.Ax + (size_t)row0 * D_, 18432, sb + B_XR);
    }
    for (int i = 0; i < 6; i++) { mbar_init(sb + B_FULL + 8 * i, 1); mbar_init(sb + B_EMPTY + 8 * i, 8); }
    mbar_init(sb + B_X, 1); mbar_init(sb + B_PFREE, 1); mbar_init(sb + B_LFREE, 8);
    mbar_init(sb + B_W, 1); mbar_init(sb + B_AUX, 3);
    mbar_expect_tx(sb + B_X, 49152);
    asm volatile("fence.mbarrier_init.release.cluster;" ::: "memory");
  } else if (tid == 32 && !isG) {
    for (int i = 0; i < 7; i++) { mbar_init(sb + B3_FULL + 8 * i, 1); mbar_init(sb + B3_EMPTY + 8 * i, 8); }
    for (int i = 0; i < 4; i++) mbar_init(sb + B_F2 + 8 * i, 1);
    mbar_init(sb + B_F2DONE, 2); mbar_init(sb + B_RES3, 1);
  }
  __syncthreads();
  asm volatile("barrier.cluster.arrive.relaxed.aligned;" ::: "memory");

  if (tid == 128) STAMP(31);
  const int cl = cta >> 1;
  const int gj = cl / 18, gp = cl % 18;
  const int fc = cta - NG;

  if (warp < 4) {
    asm volatile("setmaxnreg.dec.sync.aligned.u32 56;");
    if (warp == 0) {
      const unsigned ep1 = ld_epoch(P.epoch, cta);
      uint32_t st = 0, ph = 1;
      if (isG) {
        if (lane == 0) { prefetch_map(&P.tW1); prefetch_map(&P.tH); prefetch_map(&P.tW2); prefetch_map(&P.tU); }
        const int ft = gp + 18 * rank;
        if (lane == 0) {
#pragma unroll 1
          for (int s = 0; s < 4; s++) {
            const uint32_t tgo = s == 0 ? 0u : W1T1 + W1DT * (uint32_t)(s - 1);
            while ((uint32_t)clock() - c_start < tgo) {}
            mbar_expect_tx(sb + B_FULL + 8 * s, STAGE_BYTES);
            tma2d(sb + s * STAGE_BYTES, &P.tW1, ft * 128, s * 64, sb + B_FULL + 8 * s);
            tma2d(sb + s * STAGE_BYTES + 8192, &P.tW1, ft * 128 + 64, s * 64, sb + B_FULL + 8 * s);
          }
        }
        __syncwarp();
        uint32_t ready = 0;
#pragma unroll 1
        for (int kb = 0; kb < 32; kb++) {
          const uint32_t sa = sb + st * STAGE_BYTES, fb = sb + B_FULL + 8 * st;
          if (kb >= 4) {
            mbar_wait(sb + B_EMPTY + 8 * st, ph, 2);
            if (lane == 0) {
              mbar_expect_tx(fb, STAGE_BYTES);
              tma2d(sa, &P.tW1, ft * 128, kb * 64, fb);
              tma2d(sa + 8192, &P.tW1, ft * 128 + 64, kb * 64, fb);
            }
          }
          if (!((ready >> kb) & 1)) { ready = poll_mask(P.flags, FL_H, 32, ep1 * 4, kb, 3); if (kb == 0 && lane == 0) STAMP(23); }
          if (lane == 0) {
#pragma unroll
            for (int i = 0; i < 3; i++) tma2d(sa + 16384 + i * 8192, &P.tH, gj * 192 + i * 64, kb * 64, fb);
            if (W2PF > 0 && kb >= 32 - W2PF && gp < 16) w2_prefetch(P, kb - (32 - W2PF), gp, gj, rank);
          }
          __syncwarp();
          if (++st == 4) { st = 0; ph ^= 1; }
        }
        if (lane == 0) STAMP(8);
        if (gp < 16) {
          ready = 0;
#pragma unroll 1
          for (int i2 = 0; i2 < 36; i2++) {
            const int n2 = i2 >> 1;
            const int tl = n2 == 0 ? gp : (n2 - 1 < gp ? n2 - 1 : n2);
            const int f0 = (18 * rank + tl) * 128 + (i2 & 1) * 64;
            const uint32_t sa = sb + st * STAGE_BYTES, fb = sb + B_FULL + 8 * st;
            mbar_wait(sb + B_EMPTY + 8 * st, ph, 4);
            if (lane == 0) {
              mbar_expect_tx(fb, i2 < 2 ? 16384 : STAGE_BYTES);
              tma2d(sa, &P.tW2, gp * 128, f0, fb);
              tma2d(sa + 8192, &P.tW2, gp * 128 + 64, f0, fb);
            }
            if (W2PF > 0 && lane == 0 && i2 + W2PF < 36) w2_prefetch(P, i2 + W2PF, gp, gj, rank);
            if (i2 >= 2) {
              if (!((ready >> tl) & 1)) ready = poll_mask(P.flags, FL_U + gj * 36 + 18 * rank, 18, ep1, tl, 5);
              if (lane == 0) {
#pragma unroll
                for (int i = 0; i < 3; i++) tma2d(sa + 16384 + i * 8192, &P.tU, gj * 192 + i * 64, f0, fb);
              }
            }
            __syncwarp();
            if (++st == 4) { st = 0; ph ^= 1; }
          }
        }
      } else {
        if (cta < 128) {
          bar_sync(5, 288);
          if (lane == 0) { STAMP(17); red_release(P.flags + (FL_H + (row0 >> 6)) * 32, 1u); STAMP(22); }
        }
        if (lane == 0) {
          prefetch_map(&P.tXB); prefetch_map(&P.tX1c); prefetch_map(&P.tZT); prefetch_map(&P.tTI);
          {
            const int part = (fc & 2) ? S_ : 0;
#pragma unroll 1
            for (int sblk = fc >> 2; sblk < 16; sblk += 6) {
              wait_flag(P.flags, FL_XB + sblk, ep1 * 8, 7);
              fence_async_glb();
#pragma unroll 1
              for (int kb = 0; kb < 5; kb++) {
                const uint32_t fb = sb + B_FULL + 8 * st;
                mbar_wait(sb + B_EMPTY + 8 * st, ph, 8);
                mbar_expect_tx(fb, 16384);
                tma2d(sb + F1_RING + st * 16384, &P.tXB, kb * 64, part + sblk * 128, fb);
                if (++st == 6) { st = 0; ph ^= 1; }
              }
            }
          }
          STAMP(8);
          wait_flag(P.flags, FL_X1, ep1 * 48, 9);
          fence_async_glb();
#pragma unroll 1
          for (int b = 0; b < 2; b++)
#pragma unroll 1
            for (int w = 0; w < 2; w++) {
              const uint32_t bar = sb + B_F2 + 8 * (w * 2 + b);
              mbar_expect_tx(bar, 24576);
              for (int c = 0; c < 3; c++) {
                const int cc = w * 144 + fc * 6 + b * 3 + c;
                tma3d(sb + w * 65536 + (b * 3 + c) * 8192, &P.tX1c, 0, 0, 2 * cc, bar);
              }
            }
          STAMP(9);
          wait_flag(P.flags, FL_TI, ep1 * 72, 6);
          fence_async_glb();
          mbar_wait(sb + B_F2DONE, 0, 24);
          mbar_expect_tx(sb + B_RES3, 110592);
#pragma unroll 1
          for (int kb = 0; kb < 9; kb++) tma2d(sb + kb * 12288, &P.tTI, kb * 64, (fc % 3) * 96, sb + B_RES3);
          wait_flag(P.flags, FL_Z, ep1 * 48, 10);
          fence_async_glb();
          STAMP(10);
          st = 0; ph = 1;
#pragma unroll 1
          for (int it = 0; it < 2; it++) {
            const int sblk = fc / 3 + 8 * it;
#pragma unroll 1
            for (int kb = 0; kb < 9; kb++) {
              const uint32_t sa = sb + F3_RING + st * 16384, fb = sb + B3_FULL + 8 * st;
              mbar_wait(sb + B3_EMPTY + 8 * st, ph, 11);
              mbar_expect_tx(fb, 16384);
              tma2d(sa, &P.tZT, sblk * 128, kb * 64, fb);
              tma2d(sa + 8192, &P.tZT, sblk * 128 + 64, kb * 64, fb);
              if (++st == 7) { st = 0; ph ^= 1; }
            }
          }
        }
        __syncwarp();
      }
    } else {
      if (cta < 128) {
        if (warp == 2) {
          if (isG && lane == 0) {
            const uint32_t dly = XDLY0 + XDLY1 * (uint32_t)cta;
            while ((uint32_t)clock() - c_start < dly) {}
            mbar_expect_tx(sb + B_XR, 18432);
            bulk_ld(side, P.Ax + (size_t)row0 * D_, 18432, sb + B_XR);
          }
          __syncwarp();
        }
        bar_sync(11, 352);
        if (warp == 2 && lane == 0) {
          STAMP(21);
          fence_gpu();
          if (isG) red_relaxed(P.flags + (FL_H + (row0 >> 6)) * 32, 1u);
          red_relaxed(P.flags + (FL_XB + (row0 >> 7)) * 32, 1u);
          STAMP(35);
        }
        if (warp == 2 && lane == 0) {
          const int j0 = 64 * (cta >> 2) + 8 * (cta & 3);
          mbar_expect_tx(sb + B_W, 4 * 4624);
          bulk_ld(side, P.Wr + (size_t)j0 * DF_, 4624, sb + B_W);
          bulk_ld(side + 4624, P.Wr + (size_t)(j0 + 32) * DF_, 4624, sb + B_W);
          bulk_ld(side + 9248, P.Wi + (size_t)j0 * DF_, 4624, sb + B_W);
          bulk_ld(side + 13872, P.Wi + (size_t)(j0 + 32) * DF_, 4624, sb + B_W);
        }
        __syncwarp();
        w_job(P, sb, side, cta, tid - 32, lane);
      } else if (lane == 0) {
        mbar_arrive(sb + B_AUX);
      }
      if (!isG) {
        ti_gen(P, fc, tid - 32, lane);
        if (warp == 1) {
#pragma unroll 1
          for (int it = 0; it < 2; it++) {
            bar_sync(7, 288);
            if (lane == 0) red_release(P.flags + (FL_A + (fc / 3 + 8 * it) * 3 + fc % 3) * 32, 1u);
            __syncwarp();
          }
        }
      }
      if (lane == 0 && warp == 3) STAMP(11);
      if (warp == 1 && isG) {
        bar_sync(1, 288);
        if (lane == 0) {
          const int ft = gp + 18 * rank;
#pragma unroll
          for (int w = 0; w < 2; w++)
#pragma unroll
            for (int i = 0; i < 3; i++) tma2d_st(&P.tU, sb + SM_STG + w * 24576 + i * 8192, gj * 192 + i * 64, ft * 128 + w * 64);
          bulk_commit();
          STAMP(29);
          bulk_wait0();
          STAMP(30);
          fence_async_glb();
          red_release(P.flags + (FL_U + gj * 36 + ft) * 32, 1u);
          STAMP(15);
          if (gp < 16) {
            mbar_wait(sb + B_LFREE, 0, 12);
            asm volatile("barrier.cluster.wait.acquire;" ::: "memory");
            mbar_arrive_remote(mapa(sb + B_PFREE, rank ^ 1));
          }
        }
      }
    }
  } else {
    asm volatile("setmaxnreg.inc.sync.aligned.u32 224;");
    const int cw = warp - 4;
    const int wg = cw >> 2, wq = cw & 3;
    const int ct = tid - 128;
    const int q4 = lane & 3, r8 = lane >> 2;
    const unsigned ep0 = ld_epoch_raw(P.epoch, cta);
    if (cta < 128) {
      uint32_t lo[2][5], hi[2][5], gl[5], gh[5];
      const uint32_t* gw = reinterpret_cast<const uint32_t*>(P.gw) + lane;
#pragma unroll
      for (int i = 0; i < 5; i++) { gl[i] = (i < 4 || lane < 16) ? __ldg(gw + 32 * i) : 0u; gh[i] = (i < 4 || lane < 16) ? __ldg(gw + 144 + 32 * i) : 0u; }
      if (ct == 0) STAMP(16);
      mbar_wait(sb + B_XR, 0, 27);
      if (ct == 0) STAMP(33);
      pair_load(side + cw * 2304, lane, lo, hi);
      ln_pair(P, row0 + cw * 2, lane, lo, hi);
      if (ct == 0) STAMP(18);
      if (!isG) bar_arrive(5, 288);
      xb_pair(P, row0 + cw * 2, lane, lo, hi, gl, gh);
      bar_arrive(11, 352);
    }
    if (ct == 0) STAMP(0);
    unsigned ep1;
    asm volatile("add.u32 %0, %1, 1;" : "=r"(ep1) : "r"(ep0));
    uint32_t st = 0, ph = 0;
    if (isG) {
      const int ft = gp + 18 * rank;
      const uint32_t bias0 = dup_bf(P.b1 + ft * 128 + wg * 64 + wq * 16 + r8), bias1 = dup_bf(P.b1 + ft * 128 + wg * 64 + wq * 16 + r8 + 8);
      float acc[96];
      const uint64_t dA0 = mkdesc(sb + wg * 8192, 8192, 1024), dB0 = mkdesc(sb + 16384, 8192, 1024);
      uint32_t prev = 0;
#pragma unroll 1
      for (int kb = 0; kb < 32; kb++) {
        mbar_wait(sb + B_FULL + 8 * st, ph, 13);
        if (kb == 0 && ct == 0) STAMP(1);
        const uint64_t so = (uint64_t)(st * (STAGE_BYTES >> 4));
        wg_fence();
#pragma unroll
        for (int kk = 0; kk < 4; kk++) wg_ss_n192<1, 1>(acc, dA0 + so + kk * 128, dB0 + so + kk * 128, (kb | kk) != 0);
        wg_commit();
        if (kb > 0) { wg_wait<1>(); if (lane == 0) mbar_arrive(sb + B_EMPTY + 8 * prev); }
        prev = st;
        if (++st == 4) { st = 0; ph ^= 1; }
      }
      wg_wait<0>();
      if (lane == 0) mbar_arrive(sb + B_EMPTY + 8 * prev);
      if (ct == 0) STAMP(2);
      {
        const int jm = lane >> 3, i8 = lane & 7;
        const uint32_t row = wq * 16 + (jm & 1) * 8 + i8;
        const uint32_t base = sb + SM_STG + wg * 24576 + row * 128;
#pragma unroll
        for (int G = 0; G < 24; G += 2) {
          uint32_t r[4];
#pragma unroll
          for (int m = 0; m < 4; m++) {
            const uint32_t x = badd2(pack2(acc[4 * G + 2 * m], acc[4 * G + 2 * m + 1]), (m & 1) ? bias1 : bias0);
            r[m] = pack2(gelu_tanh(bf_lo(x)), gelu_tanh(bf_hi(x)));
          }
          const uint32_t grp = G + (jm >> 1);
          stsm4(base + (grp >> 3) * 8192 + (((grp & 7) ^ i8) << 4), r[0], r[1], r[2], r[3]);
        }
      }
      fence_async_smem();
      bar_sync(1, 288);
      if (ct == 0) STAMP(3);
      if (gp < 16) {
        const uint64_t dS0 = mkdesc(sb + SM_STG, 8192, 1024);
#pragma unroll 1
        for (int i2 = 0; i2 < 36; i2++) {
          mbar_wait(sb + B_FULL + 8 * st, ph, 14);
          const uint64_t so = (uint64_t)(st * (STAGE_BYTES >> 4));
          const uint64_t db = i2 < 2 ? dS0 + (uint64_t)(i2 * (24576 >> 4)) : dB0 + so;
          wg_fence();
#pragma unroll
          for (int kk = 0; kk < 4; kk++) wg_ss_n192<1, 1>(acc, dA0 + so + kk * 128, db + kk * 128, (i2 | kk) != 0);
          wg_commit();
          if (i2 > 0) {
            wg_wait<1>();
            if (lane == 0) { mbar_arrive(sb + B_EMPTY + 8 * prev); if (i2 == 2) mbar_arrive(sb + B_LFREE); }
          }
          if (ct == 0 && (i2 == 2 || i2 == 3 || i2 == 4 || i2 == 8 || i2 == 16)) STAMP(i2 == 2 ? 24 : i2 == 3 ? 25 : i2 == 4 ? 26 : i2 == 8 ? 27 : 28);
          prev = st;
          if (++st == 4) { st = 0; ph ^= 1; }
        }
        wg_wait<0>();
        if (ct == 0) STAMP(4);
        asm volatile("barrier.cluster.wait.acquire;" ::: "memory");
        mbar_wait_cl(sb + B_PFREE, 0, 15);
        {
          const uint32_t rdst = mapa(sb + SM_STG + ct * 16, rank ^ 1), rbar = mapa(sb + B_X, rank ^ 1);
          if (rank == 0) {
#pragma unroll
            for (int i = 0; i < 12; i++)
              asm volatile("st.async.weak.shared::cluster.mbarrier::complete_tx::bytes.v4.f32 [%0], {%1, %2, %3, %4}, [%5];"
                           ::"r"(rdst + i * 4096), "f"(acc[48 + 4 * i]), "f"(acc[49 + 4 * i]), "f"(acc[50 + 4 * i]), "f"(acc[51 + 4 * i]), "r"(rbar) : "memory");
          } else {
#pragma unroll
            for (int i = 0; i < 12; i++)
              asm volatile("st.async.weak.shared::cluster.mbarrier::complete_tx::bytes.v4.f32 [%0], {%1, %2, %3, %4}, [%5];"
                           ::"r"(rdst + i * 4096), "f"(acc[4 * i]), "f"(acc[1 + 4 * i]), "f"(acc[2 + 4 * i]), "f"(acc[3 + 4 * i]), "r"(rbar) : "memory");
#pragma unroll
            for (int i = 0; i < 48; i++) acc[i] = acc[48 + i];
          }
        }
        const int cb = 2 * gj + rank;
        const int srow = gp * 128 + wg * 64 + wq * 16 + r8;
        if (lane == 0) { wait_flag(P.flags, FL_XB + gp, ep1 * 8, 16); wait_flag(P.flags, FL_A + gp * 3 + (cb % 3), ep1, 17); }
        __syncwarp();
        uint4 af[6];
#pragma unroll
        for (int i = 0; i < 6; i++) af[i] = __ldcg(P.afrag + ((size_t)(gp * 6 + cb) * 6 + i) * 256 + ct);
        const float gf0 = __ldcg(P.gate + srow), gf1 = __ldcg(P.gate + srow + 8);
        const uint32_t g0 = pack2(gf0, gf0), g1 = pack2(gf1, gf1), og0 = pack2(1.0f - gf0, 1.0f - gf0), og1 = pack2(1.0f - gf1, 1.0f - gf1);
        const uint32_t c0 = dup_bf(P.b2 + srow), c1 = dup_bf(P.b2 + srow + 8);
        bar_sync(4, 256);
        mbar_wait_cl(sb + B_X, 0, 18);
        if (ct == 0) STAMP(5);
        {
          const int jm = lane >> 3, i8 = lane & 7;
          const uint32_t row = wq * 16 + (jm & 1) * 8 + i8;
          const uint32_t obase = sb + wg * 12288 + row * 64;
#pragma unroll
          for (int i = 0; i < 6; i++) {
            float v[8];
#pragma unroll
            for (int hh = 0; hh < 2; hh++) {
              float4 pz;
              asm volatile("ld.shared.v4.f32 {%0, %1, %2, %3}, [%4];" : "=f"(pz.x), "=f"(pz.y), "=f"(pz.z), "=f"(pz.w) : "r"(sb + SM_STG + ct * 16 + (2 * i + hh) * 4096));
              v[4 * hh] = acc[8 * i + 4 * hh] + pz.x; v[4 * hh + 1] = acc[8 * i + 4 * hh + 1] + pz.y;
              v[4 * hh + 2] = acc[8 * i + 4 * hh + 2] + pz.z; v[4 * hh + 3] = acc[8 * i + 4 * hh + 3] + pz.w;
            }
            const uint32_t aw[4] = {af[i].x, af[i].y, af[i].z, af[i].w};
            uint32_t r[4];
#pragma unroll
            for (int m = 0; m < 4; m++) {
              const uint32_t bb = badd2(pack2(v[2 * m], v[2 * m + 1]), (m & 1) ? c1 : c0);
              r[m] = badd2(bmul2((m & 1) ? g1 : g0, aw[m]), bmul2((m & 1) ? og1 : og0, bb));
            }
            const uint32_t grp = 2 * i + (jm >> 1);
            stsm4(obase + (grp >> 2) * 4096 + (((grp & 3) ^ ((row >> 1) & 3)) << 4), r[0], r[1], r[2], r[3]);
          }
        }
        fence_async_smem();
        bar_sync(2 + wg, 128);
        if ((ct & 127) == 0) {
#pragma unroll
          for (int i = 0; i < 3; i++) tma2d_st(&P.tOut, sb + wg * 12288 + i * 4096, cb * 96 + i * 32, gp * 128 + wg * 64);
          bulk_commit();
          bulk_wait0_read();
        }
        if (ct == 0) STAMP(6);
      }
      if (ct == 0) P.epoch[cta * 32] = ep1;
    } else {
      b1_gen(sb, fc & 3, cw, lane);
      fence_async_smem();
      bar_sync(4, 256);
      if (ct == 0) STAMP(1);
      const int jm = lane >> 3, i8 = lane & 7;
      {
        const uint64_t dA0 = mkdesc(sb + F1_RING + wg * 8192, 16, 1024), dB0 = mkdesc(sb, 16, 1024);
        float acc[72];
        bool first = true;
#pragma unroll 1
        for (int sblk = fc >> 2; sblk < 16; sblk += 6) {
          uint32_t prev = 0;
#pragma unroll 1
          for (int kb = 0; kb < 4; kb++) {
            mbar_wait(sb + B_FULL + 8 * st, ph, 19);
            if (ct == 0 && sblk >= 6 && sblk < 12 && kb == 0) STAMP(29);
            const uint64_t ao = dA0 + (uint64_t)(st * 1024), bo = dB0 + (uint64_t)(kb * 1152);
            wg_fence();
            wg_ss_n144<0, 0>(acc, ao, bo, kb != 0);
            wg_ss_n144<0, 0>(acc, ao + 2, bo + 2, 1);
            wg_ss_n144<0, 0>(acc, ao + 4, bo + 4, 1);
            wg_ss_n144<0, 0>(acc, ao + 6, bo + 6, 1);
            wg_commit();
            if (kb > 0) { wg_wait<1>(); if (lane == 0) mbar_arrive(sb + B_EMPTY + 8 * prev); }
            prev = st;
            if (++st == 6) { st = 0; ph ^= 1; }
          }
          {
            mbar_wait(sb + B_FULL + 8 * st, ph, 19);
            if (ct == 0 && sblk >= 6 && sblk < 12) STAMP(30);
            const uint64_t ao = dA0 + (uint64_t)(st * 1024), bo = dB0 + (uint64_t)(4 * 1152);
            wg_fence();
            wg_ss_n144<0, 0>(acc, ao, bo, 1);
            wg_ss_n144<0, 0>(acc, ao + 2, bo + 2, 1);
            wg_commit();
            wg_wait<1>();
            if (lane == 0) mbar_arrive(sb + B_EMPTY + 8 * prev);
            prev = st;
            if (++st == 6) { st = 0; ph ^= 1; }
          }
          wg_wait<0>();
          if (lane == 0) mbar_arrive(sb + B_EMPTY + 8 * prev);
          if (first) { mbar_wait(sb + B_AUX, 0, 20); first = false; }
          if ((ct & 127) == 0) bulk_wait0_read();
          bar_sync(2 + wg, 128);
          const uint32_t base = sb + F1_STG + wg * 18432;
#pragma unroll
          for (int G = 0; G < 18; G += 2) {
            const uint32_t row = 8 * (G + (jm >> 1)) + i8;
            stsm4t(base + row * 128 + (((2 * wq + (jm & 1)) ^ i8) << 4), pack2(acc[4 * G], acc[4 * G + 1]), pack2(acc[4 * G + 2], acc[4 * G + 3]),
                   pack2(acc[4 * G + 4], acc[4 * G + 5]), pack2(acc[4 * G + 6], acc[4 * G + 7]));
          }
          fence_async_smem();
          bar_sync(2 + wg, 128);
          if ((ct & 127) == 0) { tma2d_st(&P.tX1s, base, sblk * 128 + wg * 64, (fc & 3) * 144); bulk_commit(); }
          if (ct == 0) STAMP(25 + sblk / 6);
        }
        bar_sync(4, 256);
        if (ct >= 64 && ct < 128) {
          asm volatile("st.shared.u16 [%0], %1;" ::"r"(sb + F_LUT + (ct - 64) * 2), "h"((uint16_t)pack2(cos_frac(ct - 64, 64), 0.f)) : "memory");
        }
        if ((ct & 127) == 0) { bulk_wait0(); if (ct == 0) STAMP(24); fence_async_glb(); red_release(P.flags + FL_X1 * 32, 1u); }
        if (wq >= 2) bar_sync(8, 128);
      }
      if (ct == 0) STAMP(2);
      {
        if (wq >= 2) f2_consts(sb, wg * 64 + (ct & 127) - 64);
        const int j1 = 8 * wq + r8;
        const uint32_t atab = sb + F_ATAB + (ct & 127) * 16;
        float twc[16], tws[16];
#pragma unroll
        for (int i = 0; i < 16; i++) {
          const int an = j1 * (8 * (i >> 1) + 2 * q4 + (i & 1));
          twc[i] = cos_frac(an, 2048); tws[i] = sin_frac(an, 2048);
        }
        fence_async_smem();
        if (lane == 0) wait_flag(P.flags, FL_WT, ep1 * 384, 21);
        bar_sync(4, 256);
        const uint64_t dC = mkdesc(sb + F_C64, 16, 1024);
        const uint32_t wbase = sb + wg * 65536;
        const uint32_t strow = (16 * wq + 8 * (jm & 1) + i8) * 128;
        constexpr float SCALE = 2.0f / (2048.0f * 576.0f);
        const uint2* wp = reinterpret_cast<const uint2*>(P.Wt + (size_t)(wg * 144 + fc * 6) * 2048) + q4 * 32 + j1;
        uint2 Wn[8];
#pragma unroll
        for (int G = 0; G < 8; G++) Wn[G] = __ldcg(wp + G * 128);
#pragma unroll 1
        for (int c = 0; c < 6; c++) {
          const uint32_t xbuf = wbase + c * 8192, tbuf = wbase + 49152 + (c & 1) * 8192;
          const int cc = wg * 144 + fc * 6 + c;
          uint2 Wv[8];
#pragma unroll
          for (int G = 0; G < 8; G++) Wv[G] = Wn[G];
          if (c < 5) {
            wp += 1024;
#pragma unroll
            for (int G = 0; G < 8; G++) Wn[G] = __ldcg(wp + G * 128);
          }
          uint32_t A[16];
#pragma unroll
          for (int t = 0; t < 4; t++)
            asm volatile("ld.shared.v4.b32 {%0, %1, %2, %3}, [%4];" : "=r"(A[4 * t]), "=r"(A[4 * t + 1]), "=r"(A[4 * t + 2]), "=r"(A[4 * t + 3]) : "r"(atab + t * 2048));
          if (c == 0 || c == 3) mbar_wait(sb + B_F2 + 8 * (wg * 2 + (c != 0)), 0, 22);
          const bool stm = (ct == 0 && c == 2);
          if (stm) STAMP(5);
          {
            float acc[32];
            const uint64_t dX = mkdesc(xbuf, 8192, 1024);
            wg_fence();
#pragma unroll
            for (int t = 0; t < 4; t++) wg_rs_n64<1>(acc, A[4 * t], A[4 * t + 1], A[4 * t + 2], A[4 * t + 3], dX + t * 128, t != 0);
            wg_commit();
            wg_wait<0>();
#pragma unroll
            for (int G = 0; G < 8; G++) {
              const float* a = &acc[4 * G];
              const float c0 = twc[2 * G], s0 = tws[2 * G], c1 = twc[2 * G + 1], s1 = tws[2 * G + 1];
              A[4 * (G >> 1) + 2 * (G & 1)] = pack2(a[0] * c0 + a[2] * s0, a[1] * c1 + a[3] * s1);
              A[4 * (G >> 1) + 2 * (G & 1) + 1] = pack2(a[2] * c0 - a[0] * s0, a[3] * c1 - a[1] * s1);
            }
          }
          float acc[64];
          wg_fence();
#pragma unroll
          for (int t = 0; t < 4; t++) wg_rs_n128<0>(acc, A[4 * t], A[4 * t + 1], A[4 * t + 2], A[4 * t + 3], dC + t * 2, t != 0);
          wg_commit();
          wg_wait<0>();
          if (cc == 0) {
            const uint32_t scr = sb + 131072;
#pragma unroll
            for (int g = 0; g < 16; g++) {
              const int j = j1 + 32 * (8 * (g >> 1) + 2 * q4 + (g & 1));
              asm volatile("st.shared.v2.f32 [%0], {%1, %2};" ::"r"(scr + j * 8), "f"(acc[4 * g] + acc[4 * g + 3]), "f"(acc[4 * g + 2] - acc[4 * g + 1]) : "memory");
            }
            bar_sync(2 + wg, 128);
#pragma unroll
            for (int G = 0; G < 8; G++) {
              float pr[2], pi[2];
#pragma unroll
              for (int e = 0; e < 2; e++) {
                const int g = 2 * G + e;
                const int j = j1 + 32 * (8 * G + 2 * q4 + e), jn = (S_ - j) & (S_ - 1);
                float nr, ni;
                asm volatile("ld.shared.v2.f32 {%0, %1}, [%2];" : "=f"(nr), "=f"(ni) : "r"(scr + jn * 8));
                const uint2 wa = __ldcg(P.W0 + j), wb = __ldcg(P.W0 + jn);
                const float h0r = bf_lo(wa.x) + bf_lo(wb.x), h0i = bf_hi(wa.x) - bf_hi(wb.x), h1r = bf_lo(wa.y) + bf_lo(wb.y), h1i = bf_hi(wa.y) - bf_hi(wb.y);
                const float4 uv = make_float4(0.125f * (h0r + h1r), 0.125f * (h0i + h1i), 0.125f * (h0r - h1r), 0.125f * (h0i - h1i));
                const float xr = acc[4 * g] + acc[4 * g + 3], xi = acc[4 * g + 2] - acc[4 * g + 1];
                pr[e] = uv.x * xr - uv.y * xi + uv.z * nr + uv.w * ni;
                pi[e] = uv.x * xi + uv.y * xr + uv.w * nr - uv.z * ni;
              }
              A[4 * (G >> 1) + 2 * (G & 1)] = pack2(pr[0], pr[1]);
              A[4 * (G >> 1) + 2 * (G & 1) + 1] = pack2(pi[0], pi[1]);
            }
          } else {
#pragma unroll
            for (int G = 0; G < 8; G++) {
              const float* a = &acc[8 * G];
              const float x0r = a[0] + a[3], x0i = a[2] - a[1], x1r = a[4] + a[7], x1i = a[6] - a[5];
              const float w0r = bf_lo(Wv[G].x), w0i = bf_hi(Wv[G].x), w1r = bf_lo(Wv[G].y), w1i = bf_hi(Wv[G].y);
              A[4 * (G >> 1) + 2 * (G & 1)] = pack2(x0r * w0r - x0i * w0i, x1r * w1r - x1i * w1i);
              A[4 * (G >> 1) + 2 * (G & 1) + 1] = pack2(x0r * w0i + x0i * w0r, x1r * w1i + x1i * w1r);
            }
          }
          wg_fence();
#pragma unroll
          for (int t = 0; t < 4; t++) wg_rs_n128<0>(acc, A[4 * t], A[4 * t + 1], A[4 * t + 2], A[4 * t + 3], dC + t * 2, t != 0);
          wg_commit();
#pragma unroll
          for (int t = 0; t < 4; t++)
            asm volatile("ld.shared.v4.b32 {%0, %1, %2, %3}, [%4];" : "=r"(Wv[2 * t].x), "=r"(Wv[2 * t].y), "=r"(Wv[2 * t + 1].x), "=r"(Wv[2 * t + 1].y) : "r"(atab + 8192 + t * 2048));
          wg_wait<0>();
#pragma unroll
          for (int G = 0; G < 8; G += 2) {
            uint32_t r[4];
#pragma unroll
            for (int h = 0; h < 2; h++) {
              const float* a = &acc[8 * (G + h)];
              const float v0r = (a[0] - a[3]) * SCALE, v0i = (a[2] + a[1]) * SCALE, v1r = (a[4] - a[7]) * SCALE, v1i = (a[6] + a[5]) * SCALE;
              const float c0 = twc[2 * (G + h)], s0 = tws[2 * (G + h)], c1 = twc[2 * (G + h) + 1], s1 = tws[2 * (G + h) + 1];
              r[2 * h] = pack2(v0r * c0 - v0i * s0, v1r * c1 - v1i * s1);
              r[2 * h + 1] = pack2(v0i * c0 + v0r * s0, v1i * c1 + v1r * s1);
            }
            stsm4(tbuf + strow + (((G + (jm >> 1)) ^ i8) << 4), r[0], r[1], r[2], r[3]);
          }
          fence_async_smem();
          bar_sync(2 + wg, 128);
          if (c > 0 && (ct & 127) == 0) { tma3d_st(&P.tZc, xbuf - 8192, 0, 0, 2 * (cc - 1)); bulk_commit(); }
          {
            float ac2[32];
            const uint64_t dT = mkdesc(tbuf, 8192, 1024);
            wg_fence();
#pragma unroll
            for (int t = 0; t < 4; t++) wg_rs_n64<1>(ac2, Wv[2 * t].x, Wv[2 * t].y, Wv[2 * t + 1].x, Wv[2 * t + 1].y, dT + t * 128, t != 0);
            wg_commit();
            wg_wait<0>();
#pragma unroll
            for (int G = 0; G < 8; G += 2) {
              const float* a = &ac2[4 * G];
              stsm4(xbuf + strow + (((G + (jm >> 1)) ^ i8) << 4), pack2(a[0], a[1]), pack2(a[2], a[3]), pack2(a[4], a[5]), pack2(a[6], a[7]));
            }
          }
          if (stm) STAMP(7);
        }
        fence_async_smem();
        bar_sync(2 + wg, 128);
        if ((ct & 127) == 0) {
          tma3d_st(&P.tZc, wbase + 5 * 8192, 0, 0, 2 * (wg * 144 + fc * 6 + 5));
          if (ct == 0) STAMP(19);
          bulk_commit(); bulk_wait0();
          if (ct == 0) STAMP(23);
          fence_async_glb(); red_release(P.flags + FL_Z * 32, 1u);
          mbar_arrive(sb + B_F2DONE);
        }
      }
      if (ct == 0) STAMP(3);
      {
        const uint64_t dA0 = mkdesc(sb + F3_RING + wg * 8192, 8192, 1024), dB0 = mkdesc(sb, 16, 1024);
        mbar_wait(sb + B_RES3, 0, 25);
        st = 0; ph = 0;
#pragma unroll 1
        for (int it = 0; it < 2; it++) {
          const int sblk = fc / 3 + 8 * it, q = fc % 3;
          float ev[48], od[48];
          uint32_t prev = 0;
#define F3W0
#define F3W1_(KB)
#define F3_STEP(ACC0, ACC1, KB, F0, F1, REL)                                                                                      \
          {                                                                                                                        \
            mbar_wait(sb + B3_FULL + 8 * st, ph, 23);                                                                              \
            F3W1_(KB)                                                                                                              \
            const uint64_t ao = dA0 + (uint64_t)(st * 1024), bo = dB0 + (uint64_t)((KB) * 768);                                    \
            wg_fence();                                                                                                            \
            wg_ss_n96<1, 0>(ACC0, ao, bo, F0);                                                                                     \
            wg_ss_n96<1, 0>(ACC0, ao + 128, bo + 2, 1);                                                                            \
            wg_ss_n96<1, 0>(ACC1, ao + 256, bo + 4, F1);                                                                           \
            wg_ss_n96<1, 0>(ACC1, ao + 384, bo + 6, 1);                                                                            \
            wg_commit();                                                                                                           \
            if (REL) { wg_wait<1>(); if (lane == 0) mbar_arrive(sb + B3_EMPTY + 8 * prev); }                                       \
            prev = st;                                                                                                             \
            if (++st == 7) { st = 0; ph ^= 1; }                                                                                    \
          }
#pragma unroll 1
          for (int kb = 0; kb < 4; kb++) F3_STEP(ev, ev, kb, kb != 0, 1, kb > 0)
          F3_STEP(ev, od, 4, 1, 0, true)
#pragma unroll 1
          for (int kb = 5; kb < 9; kb++) F3_STEP(od, od, kb, 1, 1, true)
          wg_wait<0>();
          if (lane == 0) mbar_arrive(sb + B3_EMPTY + 8 * prev);
#pragma unroll
          for (int i = 0; i < 6; i++) {
            uint4 p, m;
            p.x = pack2(ev[8 * i] + od[8 * i], ev[8 * i + 1] + od[8 * i + 1]); m.x = pack2(ev[8 * i] - od[8 * i], ev[8 * i + 1] - od[8 * i + 1]);
            p.y = pack2(ev[8 * i + 2] + od[8 * i + 2], ev[8 * i + 3] + od[8 * i + 3]); m.y = pack2(ev[8 * i + 2] - od[8 * i + 2], ev[8 * i + 3] - od[8 * i + 3]);
            p.z = pack2(ev[8 * i + 4] + od[8 * i + 4], ev[8 * i + 5] + od[8 * i + 5]); m.z = pack2(ev[8 * i + 4] - od[8 * i + 4], ev[8 * i + 5] - od[8 * i + 5]);
            p.w = pack2(ev[8 * i + 6] + od[8 * i + 6], ev[8 * i + 7] + od[8 * i + 7]); m.w = pack2(ev[8 * i + 6] - od[8 * i + 6], ev[8 * i + 7] - od[8 * i + 7]);
            P.afrag[((size_t)(sblk * 6 + q) * 6 + i) * 256 + ct] = p;
            P.afrag[((size_t)(sblk * 6 + q + 3) * 6 + i) * 256 + ct] = m;
          }
          bar_arrive(7, 288);
          if (ct == 0 && it == 0) STAMP(6);
        }
      }
      if (ct == 0) { STAMP(4); P.epoch[cta * 32] = ep1; }
    }
  }
}

typedef CUresult (*EncFn)(CUtensorMap*, CUtensorMapDataType, cuuint32_t, void*, const cuuint64_t*, const cuuint64_t*, const cuuint32_t*,
                          const cuuint32_t*, CUtensorMapInterleave, CUtensorMapSwizzle, CUtensorMapL2promotion, CUtensorMapFloatOOBfill);

void mk2d(EncFn enc, CUtensorMap* m, const void* p, uint64_t inner, uint64_t outer, uint32_t bi, uint32_t bo, CUtensorMapSwizzle sw, uint64_t pitch = 0) {
  cuuint64_t dims[2] = {inner, outer}; cuuint64_t str[1] = {(pitch ? pitch : inner) * 2}; cuuint32_t box[2] = {bi, bo}; cuuint32_t es[2] = {1, 1};
  enc(m, CU_TENSOR_MAP_DATA_TYPE_BFLOAT16, 2, const_cast<void*>(p), dims, str, box, es, CU_TENSOR_MAP_INTERLEAVE_NONE, sw,
      CU_TENSOR_MAP_L2_PROMOTION_L2_256B, CU_TENSOR_MAP_FLOAT_OOB_FILL_NONE);
}
void mk3d(EncFn enc, CUtensorMap* m, const void* p) {
  cuuint64_t dims[3] = {64, 32, 576}; cuuint64_t str[2] = {128, 4096}; cuuint32_t box[3] = {64, 32, 2}; cuuint32_t es[3] = {1, 1, 1};
  enc(m, CU_TENSOR_MAP_DATA_TYPE_BFLOAT16, 3, const_cast<void*>(p), dims, str, box, es, CU_TENSOR_MAP_INTERLEAVE_NONE, CU_TENSOR_MAP_SWIZZLE_128B,
      CU_TENSOR_MAP_L2_PROMOTION_L2_256B, CU_TENSOR_MAP_FLOAT_OOB_FILL_NONE);
}

}

extern "C" void kernel_launch(void* const* d_in, const int* in_sizes, int n_in, void* d_out, int out_size) {
  (void)in_sizes; (void)n_in; (void)out_size;
  static EncFn enc = nullptr;
  static void *p_h, *p_u, *p_xb, *p_TI, *p_X1T, *p_ZT, *p_Wt, *p_W0, *p_af, *p_gate, *p_flags, *p_epoch;
  if (!enc) {
    void* fn = nullptr;
    cudaDriverEntryPointQueryResult qr;
    cudaGetDriverEntryPoint("cuTensorMapEncodeTiled", &fn, cudaEnableDefault, &qr);
    enc = (EncFn)fn;
    cudaFuncSetAttribute(mega_kernel, cudaFuncAttributeMaxDynamicSharedMemorySize, SM_TOTAL);
    cudaGetSymbolAddress(&p_h, g_h); cudaGetSymbolAddress(&p_u, g_u); cudaGetSymbolAddress(&p_xb, g_xb);
    cudaGetSymbolAddress(&p_TI, g_TI); cudaGetSymbolAddress(&p_Wt, g_Wt); cudaGetSymbolAddress(&p_W0, g_W0);
    cudaGetSymbolAddress(&p_af, g_afrag); cudaGetSymbolAddress(&p_gate, g_gate); cudaGetSymbolAddress(&p_flags, g_flags); cudaGetSymbolAddress(&p_epoch, g_epoch);
    cudaGetSymbolAddress(&p_X1T, g_X1T); cudaGetSymbolAddress(&p_ZT, g_ZT);
  }
  Params P;
  const CUtensorMapSwizzle S128 = CU_TENSOR_MAP_SWIZZLE_128B;
  mk2d(enc, &P.tW1, d_in[4], F_, S_, 64, 64, S128);
  mk2d(enc, &P.tH, p_h, D_, S_, 64, 64, S128);
  mk2d(enc, &P.tW2, d_in[6], S_, F_, 64, 64, S128);
  mk2d(enc, &P.tU, p_u, D_, F_, 64, 64, S128);
  mk2d(enc, &P.tOut, d_out, D_, S_, 32, 64, CU_TENSOR_MAP_SWIZZLE_64B);
  mk2d(enc, &P.tXB, p_xb, 288, 2 * S_, 64, 128, S128, 320);
  mk2d(enc, &P.tTI, p_TI, 576, 288, 64, 96, S128);
  mk2d(enc, &P.tX1s, p_X1T, S_, 576, 64, 144, S128);
  mk3d(enc, &P.tX1c, p_X1T);
  mk3d(enc, &P.tZc, p_ZT);
  mk2d(enc, &P.tZT, p_ZT, S_, 576, 64, 64, S128);
  P.Ax = (const bf16*)d_in[0]; P.Wr = (const bf16*)d_in[1]; P.Wi = (const bf16*)d_in[2];
  P.h = (bf16*)p_h; P.xb = (bf16*)p_xb; P.flags = (unsigned*)p_flags; P.epoch = (unsigned*)p_epoch; P.gate = (float*)p_gate;
  P.Wt = (uint32_t*)p_Wt; P.W0 = (uint2*)p_W0; P.TI = (bf16*)p_TI; P.afrag = (uint4*)p_af; P.stamp = nullptr;
  P.b1 = (const bf16*)d_in[5]; P.b2 = (const bf16*)d_in[7]; P.gw = (const bf16*)d_in[8];

  cudaLaunchConfig_t cfg = {};
  cfg.gridDim = dim3(NCTA); cfg.blockDim = dim3(NTHREADS); cfg.dynamicSmemBytes = SM_TOTAL; cfg.stream = cudaStreamPerThread;
  cudaLaunchAttribute at[1];
  at[0].id = cudaLaunchAttributeClusterDimension; at[0].val.clusterDim.x = 2; at[0].val.clusterDim.y = 1; at[0].val.clusterDim.z = 1;
  cfg.attrs = at; cfg.numAttrs = 1;
  cudaLaunchKernelEx(&cfg, mega_kernel, P);
}
```

```cpp
#include <cuda_runtime.h>
#include <cuda_bf16.h>
#include <cuda.h>
#include <stdint.h>

template<int TA, int TB> __device__ __forceinline__ void wg_ss_n64_o0(float (&d)[96], uint64_t da, uint64_t db) {
  asm volatile("{\n.reg .pred p;\nsetp.eq.b32 p, 0, 0;\n"
    "wgmma.mma_async.sync.aligned.m64n64k16.f32.bf16.bf16 {%0, %1, %2, %3, %4, %5, %6, %7, %8, %9, %10, %11, %12, %13, %14, %15, %16, %17, %18, %19, %20, %21, %22, %23, %24, %25, %26, %27, %28, %29, %30, %31}, %32, %33, p, 1, 1, %34, %35;\n}\n"
    : "+f"(d[0]), "+f"(d[1]), "+f"(d[2]), "+f"(d[3]), "+f"(d[4]), "+f"(d[5]), "+f"(d[6]), "+f"(d[7]), "+f"(d[8]), "+f"(d[9]), "+f"(d[10]), "+f"(d[11]), "+f"(d[12]), "+f"(d[13]), "+f"(d[14]), "+f"(d[15]), "+f"(d[16]), "+f"(d[17]), "+f"(d[18]), "+f"(d[19]), "+f"(d[20]), "+f"(d[21]), "+f"(d[22]), "+f"(d[23]), "+f"(d[24]), "+f"(d[25]), "+f"(d[26]), "+f"(d[27]), "+f"(d[28]), "+f"(d[29]), "+f"(d[30]), "+f"(d[31])
    : "l"(da), "l"(db), "n"(TA), "n"(TB));
}

template<int TA, int TB> __device__ __forceinline__ void wg_ss_n128_o0(float (&d)[64], uint64_t da, uint64_t db) {
  asm volatile("{\n.reg .pred p;\nsetp.eq.b32 p, 0, 0;\n"
    "wgmma.mma_async.sync.aligned.m64n128k16.f32.bf16.bf16 {%0, %1, %2, %3, %4, %5, %6, %7, %8, %9, %10, %11, %12, %13, %14, %15, %16, %17, %18, %19, %20, %21, %22, %23, %24, %25, %26, %27, %28, %29, %30, %31, %32, %33, %34, %35, %36, %37, %38, %39, %40, %41, %42, %43, %44, %45, %46, %47, %48, %49, %50, %51, %52, %53, %54, %55, %56, %57, %58, %59, %60, %61, %62, %63}, %64, %65, p, 1, 1, %66, %67;\n}\n"
    : "+f"(d[0]), "+f"(d[1]), "+f"(d[2]), "+f"(d[3]), "+f"(d[4]), "+f"(d[5]), "+f"(d[6]), "+f"(d[7]), "+f"(d[8]), "+f"(d[9]), "+f"(d[10]), "+f"(d[11]), "+f"(d[12]), "+f"(d[13]), "+f"(d[14]), "+f"(d[15]), "+f"(d[16]), "+f"(d[17]), "+f"(d[18]), "+f"(d[19]), "+f"(d[20]), "+f"(d[21]), "+f"(d[22]), "+f"(d[23]), "+f"(d[24]), "+f"(d[25]), "+f"(d[26]), "+f"(d[27]), "+f"(d[28]), "+f"(d[29]), "+f"(d[30]), "+f"(d[31]), "+f"(d[32]), "+f"(d[33]), "+f"(d[34]), "+f"(d[35]), "+f"(d[36]), "+f"(d[37]), "+f"(d[38]), "+f"(d[39]), "+f"(d[40]), "+f"(d[41]), "+f"(d[42]), "+f"(d[43]), "+f"(d[44]), "+f"(d[45]), "+f"(d[46]), "+f"(d[47]), "+f"(d[48]), "+f"(d[49]), "+f"(d[50]), "+f"(d[51]), "+f"(d[52]), "+f"(d[53]), "+f"(d[54]), "+f"(d[55]), "+f"(d[56]), "+f"(d[57]), "+f"(d[58]), "+f"(d[59]), "+f"(d[60]), "+f"(d[61]), "+f"(d[62]), "+f"(d[63])
    : "l"(da), "l"(db), "n"(TA), "n"(TB));
}

template<int TA, int TB> __device__ __forceinline__ void wg_ss_n192(float (&d)[96], uint64_t da, uint64_t db, int sd) {
  asm volatile("{\n.reg .pred p;\nsetp.ne.b32 p, %98, 0;\n"
    "wgmma.mma_async.sync.aligned.m64n192k16.f32.bf16.bf16 {%0, %1, %2, %3, %4, %5, %6, %7, %8, %9, %10, %11, %12, %13, %14, %15, %16, %17, %18, %19, %20, %21, %22, %23, %24, %25, %26, %27, %28, %29, %30, %31, %32, %33, %34, %35, %36, %37, %38, %39, %40, %41, %42, %43, %44, %45, %46, %47, %48, %49, %50, %51, %52, %53, %54, %55, %56, %57, %58, %59, %60, %61, %62, %63, %64, %65, %66, %67, %68, %69, %70, %71, %72, %73, %74, %75, %76, %77, %78, %79, %80, %81, %82, %83, %84, %85, %86, %87, %88, %89, %90, %91, %92, %93, %94, %95}, %96, %97, p, 1, 1, %99, %100;\n}\n"
    : "+f"(d[0]), "+f"(d[1]), "+f"(d[2]), "+f"(d[3]), "+f"(d[4]), "+f"(d[5]), "+f"(d[6]), "+f"(d[7]), "+f"(d[8]), "+f"(d[9]), "+f"(d[10]), "+f"(d[11]), "+f"(d[12]), "+f"(d[13]), "+f"(d[14]), "+f"(d[15]), "+f"(d[16]), "+f"(d[17]), "+f"(d[18]), "+f"(d[19]), "+f"(d[20]), "+f"(d[21]), "+f"(d[22]), "+f"(d[23]), "+f"(d[24]), "+f"(d[25]), "+f"(d[26]), "+f"(d[27]), "+f"(d[28]), "+f"(d[29]), "+f"(d[30]), "+f"(d[31]), "+f"(d[32]), "+f"(d[33]), "+f"(d[34]), "+f"(d[35]), "+f"(d[36]), "+f"(d[37]), "+f"(d[38]), "+f"(d[39]), "+f"(d[40]), "+f"(d[41]), "+f"(d[42]), "+f"(d[43]), "+f"(d[44]), "+f"(d[45]), "+f"(d[46]), "+f"(d[47]), "+f"(d[48]), "+f"(d[49]), "+f"(d[50]), "+f"(d[51]), "+f"(d[52]), "+f"(d[53]), "+f"(d[54]), "+f"(d[55]), "+f"(d[56]), "+f"(d[57]), "+f"(d[58]), "+f"(d[59]), "+f"(d[60]), "+f"(d[61]), "+f"(d[62]), "+f"(d[63]), "+f"(d[64]), "+f"(d[65]), "+f"(d[66]), "+f"(d[67]), "+f"(d[68]), "+f"(d[69]), "+f"(d[70]), "+f"(d[71]), "+f"(d[72]), "+f"(d[73]), "+f"(d[74]), "+f"(d[75]), "+f"(d[76]), "+f"(d[77]), "+f"(d[78]), "+f"(d[79]), "+f"(d[80]), "+f"(d[81]), "+f"(d[82]), "+f"(d[83]), "+f"(d[84]), "+f"(d[85]), "+f"(d[86]), "+f"(d[87]), "+f"(d[88]), "+f"(d[89]), "+f"(d[90]), "+f"(d[91]), "+f"(d[92]), "+f"(d[93]), "+f"(d[94]), "+f"(d[95])
    : "l"(da), "l"(db), "r"(sd), "n"(TA), "n"(TB));
}

template<int TA, int TB> __device__ __forceinline__ void wg_ss_n144(float (&d)[72], uint64_t da, uint64_t db, int sd) {
  asm volatile("{\n.reg .pred p;\nsetp.ne.b32 p, %74, 0;\n"
    "wgmma.mma_async.sync.aligned.m64n144k16.f32.bf16.bf16 {%0, %1, %2, %3, %4, %5, %6, %7, %8, %9, %10, %11, %12, %13, %14, %15, %16, %17, %18, %19, %20, %21, %22, %23, %24, %25, %26, %27, %28, %29, %30, %31, %32, %33, %34, %35, %36, %37, %38, %39, %40, %41, %42, %43, %44, %45, %46, %47, %48, %49, %50, %51, %52, %53, %54, %55, %56, %57, %58, %59, %60, %61, %62, %63, %64, %65, %66, %67, %68, %69, %70, %71}, %72, %73, p, 1, 1, %75, %76;\n}\n"
    : "+f"(d[0]), "+f"(d[1]), "+f"(d[2]), "+f"(d[3]), "+f"(d[4]), "+f"(d[5]), "+f"(d[6]), "+f"(d[7]), "+f"(d[8]), "+f"(d[9]), "+f"(d[10]), "+f"(d[11]), "+f"(d[12]), "+f"(d[13]), "+f"(d[14]), "+f"(d[15]), "+f"(d[16]), "+f"(d[17]), "+f"(d[18]), "+f"(d[19]), "+f"(d[20]), "+f"(d[21]), "+f"(d[22]), "+f"(d[23]), "+f"(d[24]), "+f"(d[25]), "+f"(d[26]), "+f"(d[27]), "+f"(d[28]), "+f"(d[29]), "+f"(d[30]), "+f"(d[31]), "+f"(d[32]), "+f"(d[33]), "+f"(d[34]), "+f"(d[35]), "+f"(d[36]), "+f"(d[37]), "+f"(d[38]), "+f"(d[39]), "+f"(d[40]), "+f"(d[41]), "+f"(d[42]), "+f"(d[43]), "+f"(d[44]), "+f"(d[45]), "+f"(d[46]), "+f"(d[47]), "+f"(d[48]), "+f"(d[49]), "+f"(d[50]), "+f"(d[51]), "+f"(d[52]), "+f"(d[53]), "+f"(d[54]), "+f"(d[55]), "+f"(d[56]), "+f"(d[57]), "+f"(d[58]), "+f"(d[59]), "+f"(d[60]), "+f"(d[61]), "+f"(d[62]), "+f"(d[63]), "+f"(d[64]), "+f"(d[65]), "+f"(d[66]), "+f"(d[67]), "+f"(d[68]), "+f"(d[69]), "+f"(d[70]), "+f"(d[71])
    : "l"(da), "l"(db), "r"(sd), "n"(TA), "n"(TB));
}

template<int TA, int TB> __device__ __forceinline__ void wg_ss_n96(float (&d)[48], uint64_t da, uint64_t db, int sd) {
  asm volatile("{\n.reg .pred p;\nsetp.ne.b32 p, %50, 0;\n"
    "wgmma.mma_async.sync.aligned.m64n96k16.f32.bf16.bf16 {%0, %1, %2, %3, %4, %5, %6, %7, %8, %9, %10, %11, %12, %13, %14, %15, %16, %17, %18, %19, %20, %21, %22, %23, %24, %25, %26, %27, %28, %29, %30, %31, %32, %33, %34, %35, %36, %37, %38, %39, %40, %41, %42, %43, %44, %45, %46, %47}, %48, %49, p, 1, 1, %51, %52;\n}\n"
    : "+f"(d[0]), "+f"(d[1]), "+f"(d[2]), "+f"(d[3]), "+f"(d[4]), "+f"(d[5]), "+f"(d[6]), "+f"(d[7]), "+f"(d[8]), "+f"(d[9]), "+f"(d[10]), "+f"(d[11]), "+f"(d[12]), "+f"(d[13]), "+f"(d[14]), "+f"(d[15]), "+f"(d[16]), "+f"(d[17]), "+f"(d[18]), "+f"(d[19]), "+f"(d[20]), "+f"(d[21]), "+f"(d[22]), "+f"(d[23]), "+f"(d[24]), "+f"(d[25]), "+f"(d[26]), "+f"(d[27]), "+f"(d[28]), "+f"(d[29]), "+f"(d[30]), "+f"(d[31]), "+f"(d[32]), "+f"(d[33]), "+f"(d[34]), "+f"(d[35]), "+f"(d[36]), "+f"(d[37]), "+f"(d[38]), "+f"(d[39]), "+f"(d[40]), "+f"(d[41]), "+f"(d[42]), "+f"(d[43]), "+f"(d[44]), "+f"(d[45]), "+f"(d[46]), "+f"(d[47])
    : "l"(da), "l"(db), "r"(sd), "n"(TA), "n"(TB));
}

template<int TB> __device__ __forceinline__ void wg_rs_n64(float (&d)[32], uint32_t a0, uint32_t a1, uint32_t a2, uint32_t a3, uint64_t db, int sd) {
  asm volatile("{\n.reg .pred p;\nsetp.ne.b32 p, %37, 0;\n"
    "wgmma.mma_async.sync.aligned.m64n64k16.f32.bf16.bf16 {%0, %1, %2, %3, %4, %5, %6, %7, %8, %9, %10, %11, %12, %13, %14, %15, %16, %17, %18, %19, %20, %21, %22, %23, %24, %25, %26, %27, %28, %29, %30, %31}, {%32, %33, %34, %35}, %36, p, 1, 1, %38;\n}\n"
    : "+f"(d[0]), "+f"(d[1]), "+f"(d[2]), "+f"(d[3]), "+f"(d[4]), "+f"(d[5]), "+f"(d[6]), "+f"(d[7]), "+f"(d[8]), "+f"(d[9]), "+f"(d[10]), "+f"(d[11]), "+f"(d[12]), "+f"(d[13]), "+f"(d[14]), "+f"(d[15]), "+f"(d[16]), "+f"(d[17]), "+f"(d[18]), "+f"(d[19]), "+f"(d[20]), "+f"(d[21]), "+f"(d[22]), "+f"(d[23]), "+f"(d[24]), "+f"(d[25]), "+f"(d[26]), "+f"(d[27]), "+f"(d[28]), "+f"(d[29]), "+f"(d[30]), "+f"(d[31])
    : "r"(a0), "r"(a1), "r"(a2), "r"(a3), "l"(db), "r"(sd), "n"(TB));
}

template<int TB> __device__ __forceinline__ void wg_rs_n128(float (&d)[64], uint32_t a0, uint32_t a1, uint32_t a2, uint32_t a3, uint64_t db, int sd) {
  asm volatile("{\n.reg .pred p;\nsetp.ne.b32 p, %69, 0;\n"
    "wgmma.mma_async.sync.aligned.m64n128k16.f32.bf16.bf16 {%0, %1, %2, %3, %4, %5, %6, %7, %8, %9, %10, %11, %12, %13, %14, %15, %16, %17, %18, %19, %20, %21, %22, %23, %24, %25, %26, %27, %28, %29, %30, %31, %32, %33, %34, %35, %36, %37, %38, %39, %40, %41, %42, %43, %44, %45, %46, %47, %48, %49, %50, %51, %52, %53, %54, %55, %56, %57, %58, %59, %60, %61, %62, %63}, {%64, %65, %66, %67}, %68, p, 1, 1, %70;\n}\n"
    : "+f"(d[0]), "+f"(d[1]), "+f"(d[2]), "+f"(d[3]), "+f"(d[4]), "+f"(d[5]), "+f"(d[6]), "+f"(d[7]), "+f"(d[8]), "+f"(d[9]), "+f"(d[10]), "+f"(d[11]), "+f"(d[12]), "+f"(d[13]), "+f"(d[14]), "+f"(d[15]), "+f"(d[16]), "+f"(d[17]), "+f"(d[18]), "+f"(d[19]), "+f"(d[20]), "+f"(d[21]), "+f"(d[22]), "+f"(d[23]), "+f"(d[24]), "+f"(d[25]), "+f"(d[26]), "+f"(d[27]), "+f"(d[28]), "+f"(d[29]), "+f"(d[30]), "+f"(d[31]), "+f"(d[32]), "+f"(d[33]), "+f"(d[34]), "+f"(d[35]), "+f"(d[36]), "+f"(d[37]), "+f"(d[38]), "+f"(d[39]), "+f"(d[40]), "+f"(d[41]), "+f"(d[42]), "+f"(d[43]), "+f"(d[44]), "+f"(d[45]), "+f"(d[46]), "+f"(d[47]), "+f"(d[48]), "+f"(d[49]), "+f"(d[50]), "+f"(d[51]), "+f"(d[52]), "+f"(d[53]), "+f"(d[54]), "+f"(d[55]), "+f"(d[56]), "+f"(d[57]), "+f"(d[58]), "+f"(d[59]), "+f"(d[60]), "+f"(d[61]), "+f"(d[62]), "+f"(d[63])
    : "r"(a0), "r"(a1), "r"(a2), "r"(a3), "l"(db), "r"(sd), "n"(TB));
}

namespace {

typedef __nv_bfloat16 bf16;

constexpr int S_ = 2048, D_ = 576, F_ = 4608, DF_ = 289;
constexpr int NCTA = 132, NG = 108, NTHREADS = 384;

constexpr uint32_t STAGE_BYTES = 40960;
constexpr uint32_t SM_STG = 163840;
constexpr uint32_t SM_SIDE = 212992;
constexpr uint32_t SM_BAR = 231680;
constexpr uint32_t SM_TOTAL = 232448;
constexpr uint32_t B_FULL = SM_BAR  , B_EMPTY = SM_BAR + 64  , B_X = SM_BAR + 128, B_X1 = SM_BAR + 136, B_LFREE = SM_BAR + 144,
                   B_W = SM_BAR + 152, B_AUX = SM_BAR + 160, B_F2 = SM_BAR + 168  , B_F2DONE = SM_BAR + 200, B_RES3 = SM_BAR + 208,
                   B3_FULL = SM_BAR + 216  , B3_EMPTY = SM_BAR + 272  , B_XR = SM_BAR + 328, B_P = SM_BAR + 336  , B_U = SM_BAR + 400  , B_HP = SM_BAR + 448;
constexpr uint32_t X_INA = 3 * STAGE_BYTES + 24576;
constexpr uint32_t X_INB = SM_STG + STAGE_BYTES;
constexpr uint32_t X_PAT = X_INB + 16384;
constexpr uint32_t X_GATE = SM_SIDE + 18176;
constexpr uint32_t X_HAND = 16384;
constexpr uint32_t X_OUT = STAGE_BYTES + 16384;
constexpr uint32_t F1_RING = 92160;
constexpr uint32_t F1_STG = 190464;
constexpr uint32_t F_XBS = F1_STG + 18560;
constexpr uint32_t F_C64 = 147456;
constexpr uint32_t F_ATAB = 163840;
constexpr uint32_t F_LUT = 180224;
constexpr uint32_t F3_RING = 110592;

constexpr int FL_H = 0, FL_U = 32, FL_XB = 140, FL_TI = 156, FL_WT = 157, FL_X1 = 158, FL_Z = 159, FL_A = 160, NFLAGS = 208;

struct Params {
  const bf16 *Ax, *gw;
  bf16 *h, *xb;
  unsigned *flags, *epoch;
  float* gate;
  const bf16 *Wr, *Wi, *b1, *b2;
  uint32_t* Wt;
  uint2* W0;
  bf16* TI;
  uint4* afrag;
  uint4* part;
  long long* stamp;
  CUtensorMap tW1, tH, tW2, tU, tU32, tOut, tXB, tTI, tX1s, tX1c, tZc, tZT;
};

}

__device__ __align__(1024) bf16 g_h[S_ * D_];
__device__ __align__(1024) bf16 g_u[F_ * D_];
__device__ __align__(1024) bf16 g_xb[2 * S_ * 320];
__device__ __align__(1024) bf16 g_TI[288 * 576];
__device__ __align__(1024) bf16 g_X1T[576 * S_];
__device__ __align__(1024) bf16 g_ZT[576 * S_];
__device__ __align__(1024) uint32_t g_Wt[288 * 2048];
__device__ __align__(1024) uint4 g_afrag[16 * 6 * 6 * 256];
__device__ __align__(1024) uint2 g_W0[2048];
__device__ __align__(1024) uint4 g_part[96 * 8 * 256];
__device__ __align__(1024) float g_gate[S_];
__device__ __align__(1024) unsigned g_flags[NFLAGS * 32];
__device__ __align__(1024) unsigned g_epoch[NCTA * 32];

#define STAMP(i) do { } while (0)
#define TGET(v) do { } while (0)
#define TPUT(i, v) do { } while (0)

namespace {

#define XDLY0 1000
#define XDLY1 5
#define W1T1 3400
#define W1DT 600
#define HGATE 4500u
#define HDT 15u
#define SKEW_KB 31
#define GDLY 500u
#define GDLY2 600u
#define NFH 4
#define PADN 24
#define W1T0 2200u

__device__ __forceinline__ bool elect_one() {
  uint32_t p;
  asm volatile("{\n.reg .pred p;\nelect.sync _|p, 0xffffffff;\nselp.u32 %0, 1, 0, p;\n}" : "=r"(p));
  return p != 0;
}
__device__ __forceinline__ uint32_t smem_u32(const void* p) { return (uint32_t)__cvta_generic_to_shared(p); }
__device__ __forceinline__ void mbar_init(uint32_t bar, uint32_t cnt) { asm volatile("mbarrier.init.shared::cta.b64 [%0], %1;" ::"r"(bar), "r"(cnt) : "memory"); }
__device__ __forceinline__ void mbar_expect_tx(uint32_t bar, uint32_t bytes) { asm volatile("mbarrier.arrive.expect_tx.shared::cta.b64 _, [%0], %1;" ::"r"(bar), "r"(bytes) : "memory"); }
__device__ __forceinline__ void mbar_arrive(uint32_t bar) { asm volatile("mbarrier.arrive.shared::cta.b64 _, [%0];" ::"r"(bar) : "memory"); }
__device__ __forceinline__ uint32_t mapa(uint32_t addr, uint32_t cta) {
  uint32_t r; asm("mapa.shared::cluster.u32 %0, %1, %2;" : "=r"(r) : "r"(addr), "r"(cta)); return r;
}
__device__ __forceinline__ void mbar_arrive_remote(uint32_t raddr) { asm volatile("mbarrier.arrive.shared::cluster.b64 _, [%0];" ::"r"(raddr) : "memory"); }
__device__ __forceinline__ void mbar_wait(uint32_t bar, uint32_t parity, int) {
  asm volatile("{\n.reg .pred p;\n.reg .u32 c;\nmov.u32 c, 0;\n"
               "LW: mbarrier.try_wait.parity.shared::cta.b64 p, [%0], %1;\n@p bra LD;\n"
               "add.u32 c, c, 1;\nsetp.lt.u32 p, c, 0x400000;\n@p bra LW;\ntrap;\nLD:\n}" ::"r"(bar), "r"(parity) : "memory");
}
__device__ __forceinline__ unsigned ld_acquire(const unsigned* p) {
  unsigned v; asm volatile("ld.acquire.gpu.global.u32 %0, [%1];" : "=r"(v) : "l"(p) : "memory"); return v;
}
__device__ __forceinline__ void st_part(uint4* p, float a, float b, float c, float d, float e, float f, uint32_t tag) {
  const uint32_t x0 = __float_as_uint(a), y0 = __float_as_uint(b), z0 = __float_as_uint(c), x1 = __float_as_uint(d), y1 = __float_as_uint(e), z1 = __float_as_uint(f);
  const uint32_t w0 = __funnelshift_r(x0, y0 >> 11, 11), w1 = __funnelshift_l(y0, __funnelshift_r(z0, tag, 11), 10);
  const uint32_t w2 = __funnelshift_r(x1, y1 >> 11, 11), w3 = __funnelshift_l(y1, __funnelshift_r(z1, tag, 11), 10);
  asm volatile("{\n.reg .b64 a, b;\nmov.b64 a, {%1, %2};\nmov.b64 b, {%3, %4};\nst.relaxed.gpu.global.v2.b64 [%0], {a, b};\n}"
               ::"l"(p), "r"(w0), "r"(w1), "r"(w2), "r"(w3) : "memory");
}
__device__ __forceinline__ void red_release(unsigned* p, unsigned v) { asm volatile("red.release.gpu.global.add.u32 [%0], %1;" ::"l"(p), "r"(v) : "memory"); }
#define FENCE_AFTER_BULK() fence_async_glb()
__device__ __forceinline__ void fence_async_glb() { asm volatile("fence.proxy.async.global;" ::: "memory"); }
__device__ __forceinline__ void fence_async_smem() { asm volatile("fence.proxy.async.shared::cta;" ::: "memory"); }
__device__ __forceinline__ unsigned ld_epoch_raw(const unsigned* epoch, int cta) {
  unsigned v; asm volatile("ld.relaxed.gpu.global.u32 %0, [%1];" : "=r"(v) : "l"(epoch + cta * 32) : "memory"); return v;
}
__device__ __forceinline__ unsigned ld_epoch(const unsigned* epoch, int cta) { return ld_epoch_raw(epoch, cta) + 1; }
__device__ __forceinline__ void red_relaxed(unsigned* p, unsigned v) { asm volatile("red.relaxed.gpu.global.add.u32 [%0], %1;" ::"l"(p), "r"(v) : "memory"); }
__device__ __forceinline__ void fence_gpu() { asm volatile("fence.acq_rel.gpu;" ::: "memory"); }
__device__ __forceinline__ void wait_flag(const unsigned* flags, int idx, unsigned target, int site) {
  const unsigned* p = flags + idx * 32;
  asm volatile("{\n.reg .pred p;\n.reg .u32 c, v;\nmov.u32 c, 0;\n"
               "LW: ld.acquire.gpu.global.u32 v, [%0];\nsub.u32 v, v, %1;\nsetp.ge.s32 p, v, 0;\n@p bra LD;\n"
               "add.u32 c, c, 1;\nsetp.lt.u32 p, c, 0x200000;\n@p bra LW;\ntrap;\nLD:\n}" ::"l"(p), "r"(target) : "memory");
}
__device__ __forceinline__ uint32_t poll_mask(const unsigned* flags, int idx0, int n, unsigned target, int need, int site) {
  const int lane = threadIdx.x & 31;
  const unsigned* p = flags + (idx0 + (lane < n ? lane : 0)) * 32;
  uint32_t m;
#pragma unroll 1
  for (uint32_t it = 0;; it++) {
    unsigned v = ld_acquire(p);
    m = __ballot_sync(0xffffffffu, (int)(v - target) >= 0);
    if (need < 0 || ((m >> need) & 1)) break;
    if (it > 0x200000u) __trap();
  }
  return m;
}

__device__ __forceinline__ void poll_u(const unsigned* flags, int idx0, int n, unsigned target, int tl, int w, uint32_t& r0, uint32_t& r1) {
  const int lane = threadIdx.x & 31;
  const unsigned* p = flags + (idx0 + (lane < n ? lane : 0)) * 32;
#pragma unroll 1
  for (uint32_t it = 0;; it++) {
    uint32_t a, b;
    asm volatile("{\n.reg .b64 v;\nld.acquire.gpu.global.b64 v, [%2];\nmov.b64 {%0, %1}, v;\n}" : "=r"(a), "=r"(b) : "l"(p) : "memory");
    r0 = __ballot_sync(0xffffffffu, (int)(a - target) >= 0);
    r1 = __ballot_sync(0xffffffffu, (int)(b - target) >= 0);
    if (((w ? r1 : r0) >> tl) & 1) break;
    if (it > 0x200000u) __trap();
  }
}
__device__ __forceinline__ void tma2d(uint32_t dst, const CUtensorMap* m, int c0, int c1, uint32_t bar) {
  asm volatile("cp.async.bulk.tensor.2d.shared::cluster.global.mbarrier::complete_tx::bytes [%0], [%1, {%3, %4}], [%2];"
               ::"r"(dst), "l"(m), "r"(bar), "r"(c0), "r"(c1) : "memory");
}
__device__ __forceinline__ void tma2d_mc(uint32_t dst, const CUtensorMap* m, int c0, int c1, uint32_t bar) {
  asm volatile("cp.async.bulk.tensor.2d.shared::cluster.global.mbarrier::complete_tx::bytes.multicast::cluster [%0], [%1, {%3, %4}], [%2], %5;"
               ::"r"(dst), "l"(m), "r"(bar), "r"(c0), "r"(c1), "h"((uint16_t)3) : "memory");
}
__device__ __forceinline__ void tma3d(uint32_t dst, const CUtensorMap* m, int c0, int c1, int c2, uint32_t bar) {
  asm volatile("cp.async.bulk.tensor.3d.shared::cluster.global.mbarrier::complete_tx::bytes [%0], [%1, {%3, %4, %5}], [%2];"
               ::"r"(dst), "l"(m), "r"(bar), "r"(c0), "r"(c1), "r"(c2) : "memory");
}
__device__ __forceinline__ void tma2d_st(const CUtensorMap* m, uint32_t src, int c0, int c1) {
  asm volatile("cp.async.bulk.tensor.2d.global.shared::cta.bulk_group [%0, {%2, %3}], [%1];" ::"l"(m), "r"(src), "r"(c0), "r"(c1) : "memory");
}
__device__ __forceinline__ void tma3d_st(const CUtensorMap* m, uint32_t src, int c0, int c1, int c2) {
  asm volatile("cp.async.bulk.tensor.3d.global.shared::cta.bulk_group [%0, {%2, %3, %4}], [%1];" ::"l"(m), "r"(src), "r"(c0), "r"(c1), "r"(c2) : "memory");
}
__device__ __forceinline__ void bulk_ld(uint32_t dst, const void* src, uint32_t bytes, uint32_t bar) {
  asm volatile("cp.async.bulk.shared::cluster.global.mbarrier::complete_tx::bytes [%0], [%1], %2, [%3];" ::"r"(dst), "l"(src), "r"(bytes), "r"(bar) : "memory");
}
__device__ __forceinline__ void bulk_st(void* dst, uint32_t src, uint32_t bytes) {
  asm volatile("cp.async.bulk.global.shared::cta.bulk_group [%0], [%1], %2;" ::"l"(dst), "r"(src), "r"(bytes) : "memory");
}
__device__ __forceinline__ void cluster_arrive() { asm volatile("barrier.cluster.arrive.relaxed.aligned;" ::: "memory"); }
__device__ __forceinline__ void cluster_wait() { asm volatile("barrier.cluster.wait.aligned;" ::: "memory"); }
__device__ __forceinline__ void bulk_commit() { asm volatile("cp.async.bulk.commit_group;" ::: "memory"); }
__device__ __forceinline__ void bulk_wait0() { asm volatile("cp.async.bulk.wait_group 0;" ::: "memory"); }
__device__ __forceinline__ void bulk_wait1() { asm volatile("cp.async.bulk.wait_group 1;" ::: "memory"); }
__device__ __forceinline__ void bulk_wait0_read() { asm volatile("cp.async.bulk.wait_group.read 0;" ::: "memory"); }
__device__ __forceinline__ void prefetch_map(const CUtensorMap* m) { asm volatile("prefetch.tensormap [%0];" ::"l"(m) : "memory"); }

__device__ __forceinline__ uint64_t mkdesc(uint32_t addr, uint32_t lbo, uint32_t sbo) {
  return (uint64_t)((addr & 0x3FFFF) >> 4) | ((uint64_t)(lbo >> 4) << 16) | ((uint64_t)(sbo >> 4) << 32) | (1ull << 62);
}
__device__ __forceinline__ void wg_fence() { asm volatile("wgmma.fence.sync.aligned;" ::: "memory"); }
__device__ __forceinline__ void wg_commit() { asm volatile("wgmma.commit_group.sync.aligned;" ::: "memory"); }
template <int N> __device__ __forceinline__ void wg_wait() { asm volatile("wgmma.wait_group.sync.aligned %0;" ::"n"(N) : "memory"); }
__device__ __forceinline__ void bar_sync(int id, int n) { asm volatile("bar.sync %0, %1;" ::"r"(id), "r"(n) : "memory"); }

__device__ __forceinline__ uint32_t pack2(float lo, float hi) {
  uint32_t r; asm("cvt.rn.bf16x2.f32 %0, %1, %2;" : "=r"(r) : "f"(hi), "f"(lo)); return r;
}
__device__ __forceinline__ float bf_lo(uint32_t v) { return __uint_as_float(v << 16); }
__device__ __forceinline__ float bf_hi(uint32_t v) { return __uint_as_float(v & 0xffff0000u); }
__device__ __forceinline__ float bfr(float x) { return bf_lo(pack2(x, 0.f)); }
__device__ __forceinline__ uint32_t badd2(uint32_t a, uint32_t b) { uint32_t r; asm("add.rn.bf16x2 %0, %1, %2;" : "=r"(r) : "r"(a), "r"(b)); return r; }
__device__ __forceinline__ uint32_t bsub2(uint32_t a, uint32_t b) { uint32_t r; asm("sub.rn.bf16x2 %0, %1, %2;" : "=r"(r) : "r"(a), "r"(b)); return r; }
__device__ __forceinline__ uint32_t bmul2(uint32_t a, uint32_t b) { uint32_t r; asm("mul.rn.bf16x2 %0, %1, %2;" : "=r"(r) : "r"(a), "r"(b)); return r; }
__device__ __forceinline__ uint32_t dup_bf(const bf16* p) { uint32_t v = *reinterpret_cast<const uint16_t*>(p); return v | (v << 16); }
__device__ __forceinline__ float cos_frac(int m, int n) { return __cosf((float)(2 * m > n ? m - n : m) * (6.283185307179586f / (float)n)); }
__device__ __forceinline__ float sin_frac(int m, int n) { return __sinf((float)(2 * m > n ? m - n : m) * (6.283185307179586f / (float)n)); }
__device__ __forceinline__ void stsm4(uint32_t addr, uint32_t a, uint32_t b, uint32_t c, uint32_t d) {
  asm volatile("stmatrix.sync.aligned.m8n8.x4.shared.b16 [%0], {%1, %2, %3, %4};" ::"r"(addr), "r"(a), "r"(b), "r"(c), "r"(d) : "memory");
}
__device__ __forceinline__ void stsm4t(uint32_t addr, uint32_t a, uint32_t b, uint32_t c, uint32_t d) {
  asm volatile("stmatrix.sync.aligned.m8n8.x4.trans.shared.b16 [%0], {%1, %2, %3, %4};" ::"r"(addr), "r"(a), "r"(b), "r"(c), "r"(d) : "memory");
}
__device__ __forceinline__ float gelu_tanh(float x) {
  float x2 = x * x;
  float z = x * fmaf(x2, 0.044715f * 0.7978845608028654f, 0.7978845608028654f);
  float t; asm("tanh.approx.f32 %0, %1;" : "=f"(t) : "f"(z));
  float hx = 0.5f * x;
  return fmaf(hx, t, hx);
}

__device__ __forceinline__ void bar_arrive(int id, int n) { asm volatile("bar.arrive %0, %1;" ::"r"(id), "r"(n) : "memory"); }
__device__ __forceinline__ void row_load(uint32_t src, int lane, uint32_t (&lo)[5], uint32_t (&hi)[5]) {
#pragma unroll
  for (int i = 0; i < 5; i++) {
    lo[i] = 0u; hi[i] = 0u;
    if (i < 4 || lane < 16) {
      asm volatile("ld.shared.u32 %0, [%1];" : "=r"(lo[i]) : "r"(src + lane * 4 + i * 128) : "memory");
      asm volatile("ld.shared.u32 %0, [%1];" : "=r"(hi[i]) : "r"(src + 576 + lane * 4 + i * 128) : "memory");
    }
  }
}
__device__ __forceinline__ void ln_row(uint32_t* h, int lane, const uint32_t (&lo)[5], const uint32_t (&hi)[5]) {
  const bool ok4 = lane < 16;
  const float c = __shfl_sync(0xffffffffu, bf_lo(lo[0]), 0);
  float s0 = 0.f, s1 = 0.f, q0 = 0.f, q1 = 0.f;
#pragma unroll
  for (int i = 0; i < 5; i++) {
    float d0 = bf_lo(lo[i]) - c, d1 = bf_hi(lo[i]) - c, d2 = bf_lo(hi[i]) - c, d3 = bf_hi(hi[i]) - c;
    if (i == 4 && !ok4) { d0 = 0.f; d1 = 0.f; d2 = 0.f; d3 = 0.f; }
    s0 += d0 + d1; s1 += d2 + d3;
    q0 = fmaf(d0, d0, fmaf(d1, d1, q0)); q1 = fmaf(d2, d2, fmaf(d3, d3, q1));
  }
  float s = s0 + s1, q = q0 + q1;
#pragma unroll
  for (int o = 16; o > 0; o >>= 1) { s += __shfl_xor_sync(0xffffffffu, s, o); q += __shfl_xor_sync(0xffffffffu, q, o); }
  const float m = s * (1.0f / 576.0f);
  const float var = fmaxf(fmaf(q, 1.0f / 576.0f, -m * m), 0.f);
  const uint32_t mb = pack2(m + c, m + c);
  float sq, rs;
  asm("sqrt.approx.f32 %0, %1;" : "=f"(sq) : "f"(bfr(bfr(var) + 1e-5f)));
  asm("rcp.approx.f32 %0, %1;" : "=f"(rs) : "f"(bfr(sq)));
#pragma unroll
  for (int i = 0; i < 5; i++) {
    const uint32_t d0 = bsub2(lo[i], mb), d1 = bsub2(hi[i], mb);
    if (i < 4 || ok4) {
      h[32 * i] = pack2(bf_lo(d0) * rs, bf_hi(d0) * rs);
      h[144 + 32 * i] = pack2(bf_lo(d1) * rs, bf_hi(d1) * rs);
    }
  }
}
__device__ __forceinline__ void pair_load(uint32_t src, int lane, uint32_t (&lo)[2][5], uint32_t (&hi)[2][5]) {
#pragma unroll
  for (int r = 0; r < 2; r++)
#pragma unroll
    for (int i = 0; i < 5; i++) {
      lo[r][i] = 0u; hi[r][i] = 0u;
      if (i < 4 || lane < 16) {
        asm volatile("ld.shared.u32 %0, [%1];" : "=r"(lo[r][i]) : "r"(src + r * 1152 + lane * 4 + i * 128) : "memory");
        asm volatile("ld.shared.u32 %0, [%1];" : "=r"(hi[r][i]) : "r"(src + r * 1152 + 576 + lane * 4 + i * 128) : "memory");
      }
    }
}
__device__ __forceinline__ void ln_pair(uint32_t* hdst, int lane, const uint32_t (&lo)[2][5], const uint32_t (&hi)[2][5]) {
  const bool ok4 = lane < 16;
  float c[2], s[2], q[2];
#pragma unroll
  for (int r = 0; r < 2; r++) c[r] = __shfl_sync(0xffffffffu, bf_lo(lo[r][0]), 0);
#pragma unroll
  for (int r = 0; r < 2; r++) {
    float s0 = 0.f, s1 = 0.f, q0 = 0.f, q1 = 0.f;
#pragma unroll
    for (int i = 0; i < 5; i++) {
      float d0 = bf_lo(lo[r][i]) - c[r], d1 = bf_hi(lo[r][i]) - c[r], d2 = bf_lo(hi[r][i]) - c[r], d3 = bf_hi(hi[r][i]) - c[r];
      if (i == 4 && !ok4) { d0 = 0.f; d1 = 0.f; d2 = 0.f; d3 = 0.f; }
      s0 += d0 + d1; s1 += d2 + d3;
      q0 = fmaf(d0, d0, fmaf(d1, d1, q0)); q1 = fmaf(d2, d2, fmaf(d3, d3, q1));
    }
    s[r] = s0 + s1; q[r] = q0 + q1;
  }
#pragma unroll
  for (int o = 16; o > 0; o >>= 1) {
#pragma unroll
    for (int r = 0; r < 2; r++) { s[r] += __shfl_xor_sync(0xffffffffu, s[r], o); q[r] += __shfl_xor_sync(0xffffffffu, q[r], o); }
  }
#pragma unroll
  for (int r = 0; r < 2; r++) {
    const float m = s[r] * (1.0f / 576.0f);
    const float var = fmaxf(fmaf(q[r], 1.0f / 576.0f, -m * m), 0.f);
    const uint32_t mb = pack2(m + c[r], m + c[r]);
    float sq, rs;
    asm("sqrt.approx.f32 %0, %1;" : "=f"(sq) : "f"(bfr(bfr(var) + 1e-5f)));
    asm("rcp.approx.f32 %0, %1;" : "=f"(rs) : "f"(bfr(sq)));
    uint32_t* h = hdst + r * 288 + lane;
#pragma unroll
    for (int i = 0; i < 5; i++) {
      const uint32_t d0 = bsub2(lo[r][i], mb), d1 = bsub2(hi[r][i], mb);
      if (i < 4 || ok4) {
        h[32 * i] = pack2(bf_lo(d0) * rs, bf_hi(d0) * rs);
        h[144 + 32 * i] = pack2(bf_lo(d1) * rs, bf_hi(d1) * rs);
      }
    }
  }
}
__device__ __forceinline__ void xb_pair_regs(const Params& P, int row, uint32_t* xdst, uint32_t plane, int lane, const uint32_t (&lo)[2][5], const uint32_t (&hi)[2][5],
                                        const uint32_t (&gl)[5], const uint32_t (&gh)[5]) {
  float z[2] = {0.f, 0.f};
#pragma unroll
  for (int r = 0; r < 2; r++) {
    uint32_t* xb = xdst + r * 160 + lane;
#pragma unroll
    for (int i = 0; i < 5; i++) {
      if (i < 4 || lane < 16) {
        xb[32 * i] = badd2(lo[r][i], hi[r][i]);
        xb[plane + 32 * i] = bsub2(lo[r][i], hi[r][i]);
      }
      const uint32_t p0 = bmul2(lo[r][i], gl[i]), p1 = bmul2(hi[r][i], gh[i]);
      z[r] += (bf_lo(p0) + bf_hi(p0)) + (bf_lo(p1) + bf_hi(p1));
    }
  }
#pragma unroll
  for (int o = 16; o > 0; o >>= 1) { z[0] += __shfl_xor_sync(0xffffffffu, z[0], o); z[1] += __shfl_xor_sync(0xffffffffu, z[1], o); }
  if (lane < 2) P.gate[row + lane] = bfr(1.0f / (1.0f + __expf(-bfr(lane ? z[1] : z[0]))));
}

__device__ __forceinline__ void xb_pair(float* gate, int rstep, uint32_t src, uint32_t* xdst, int lane, const uint32_t (&gl)[5], const uint32_t (&gh)[5]) {
  float z[2] = {0.f, 0.f};
#pragma unroll
  for (int r = 0; r < 2; r++) {
    uint32_t lo[5], hi[5];
    row_load(src + r * 9216, lane, lo, hi);
    uint32_t* xb = xdst + r * 1280 + lane;
#pragma unroll
    for (int i = 0; i < 5; i++) {
      if (i < 4 || lane < 16) {
        xb[32 * i] = badd2(lo[i], hi[i]);
        xb[2560 + 32 * i] = bsub2(lo[i], hi[i]);
      }
      const uint32_t p0 = bmul2(lo[i], gl[i]), p1 = bmul2(hi[i], gh[i]);
      z[r] += (bf_lo(p0) + bf_hi(p0)) + (bf_lo(p1) + bf_hi(p1));
    }
  }
#pragma unroll
  for (int o = 16; o > 0; o >>= 1) { z[0] += __shfl_xor_sync(0xffffffffu, z[0], o); z[1] += __shfl_xor_sync(0xffffffffu, z[1], o); }
  if (lane < 2) gate[lane * rstep] = bfr(1.0f / (1.0f + __expf(-bfr(lane ? z[1] : z[0]))));
}

__device__ __forceinline__ void w_job(const Params& P, uint32_t sb, uint32_t base, int unit, int t3, int lane) {
  mbar_wait(sb + B_W, 0, 1);
  const int w = unit & 3, jp = unit >> 2;
#pragma unroll 2
  for (int it = 0; it < 12; it++) {
    int idx = t3 + 96 * it;
    int ip = idx & 3, cc = idx >> 2;
    int k = cc < 144 ? 2 * cc : 2 * (cc - 144) + 1;
    uint32_t o[4];
#pragma unroll
    for (int ii = 0; ii < 2; ii++) {
#pragma unroll
      for (int e = 0; e < 2; e++) {
        uint32_t off = base + e * 4624 + ((2 * ip + ii) * DF_ + k) * 2;
        uint16_t wr, wi;
        asm volatile("ld.shared.u16 %0, [%1];" : "=h"(wr) : "r"(off));
        asm volatile("ld.shared.u16 %0, [%1];" : "=h"(wi) : "r"(off + 9248));
        o[ii * 2 + e] = (uint32_t)wr | ((uint32_t)wi << 16);
      }
    }
    uint4* dst = reinterpret_cast<uint4*>(P.Wt + (size_t)cc * 2048 + (jp * 32 + 8 * w + 2 * ip) * 2);
    *dst = make_uint4(o[0], o[1], o[2], o[3]);
  }
  if (t3 < 16) {
    const uint32_t off = base + (t3 >> 3) * 4624 + (t3 & 7) * DF_ * 2;
    uint16_t a, b, c, d;
    asm volatile("ld.shared.u16 %0, [%1];" : "=h"(a) : "r"(off));
    asm volatile("ld.shared.u16 %0, [%1];" : "=h"(b) : "r"(off + 9248));
    asm volatile("ld.shared.u16 %0, [%1];" : "=h"(c) : "r"(off + 576));
    asm volatile("ld.shared.u16 %0, [%1];" : "=h"(d) : "r"(off + 9248 + 576));
    P.W0[64 * jp + 8 * w + (t3 & 7) + 32 * (t3 >> 3)] = make_uint2((uint32_t)a | ((uint32_t)b << 16), (uint32_t)c | ((uint32_t)d << 16));
  }
  __syncwarp();
  if (lane == 0) { mbar_arrive(sb + B_AUX); red_release(P.flags + FL_WT * 32, 1u); }
}

__device__ __forceinline__ void cs576(float m, float& c, float& s) {
  const float q = fmaf(m, 1.0f / 576.0f, 12582912.0f) - 12582912.0f;
  const float a = fmaf(q, -576.0f, m) * (6.283185307179586f / 576.0f);
  c = __cosf(a); s = __sinf(a);
}
__device__ __forceinline__ int col_freq(int cc) { return cc < 144 ? 2 * cc : 2 * (cc - 144) + 1; }

__device__ __forceinline__ void b1_gen(uint32_t sb, int nb, int cw, int lane) {
#pragma unroll 1
  for (int rp = cw; rp < 72; rp += 8) {
    const int cc = 72 * nb + rp;
    const float kf = (float)col_freq(cc);
    float cd, sd;
    cs576(kf, cd, sd);
    const uint32_t r0 = 2 * rp;
    uint32_t a0 = sb + r0 * 128 + (((lane >> 2) ^ (r0 & 7)) << 4) + (lane & 3) * 4;
    uint32_t a1 = sb + (r0 + 1) * 128 + (((lane >> 2) ^ ((r0 + 1) & 7)) << 4) + (lane & 3) * 4;
    float m = kf * (float)(2 * lane);
#pragma unroll
    for (int kb = 0; kb < 5; kb++) {
      float c0, s0;
      cs576(m, c0, s0);
      m = fmaf(kf, 64.0f, m);
      const float c1 = c0 * cd - s0 * sd, s1 = s0 * cd + c0 * sd;
      const uint32_t w1 = cc == 0 ? 0xBF803F80u : pack2(-s0, -s1);
      if (kb < 4 || lane < 16) {
        asm volatile("st.shared.u32 [%0], %1;" ::"r"(a0 + kb * 18432), "r"(pack2(c0, c1)) : "memory");
        asm volatile("st.shared.u32 [%0], %1;" ::"r"(a1 + kb * 18432), "r"(w1) : "memory");
      }
    }
  }
}

__device__ __forceinline__ uint32_t lut2(uint32_t lut, int i0, int i1) {
  uint16_t a, b;
  asm volatile("ld.shared.u16 %0, [%1];" : "=h"(a) : "r"(lut + (i0 & 63) * 2));
  asm volatile("ld.shared.u16 %0, [%1];" : "=h"(b) : "r"(lut + (i1 & 63) * 2));
  return (uint32_t)a | ((uint32_t)b << 16);
}
__device__ __forceinline__ void f2_consts(uint32_t sb, int t) {
  const uint32_t lut = sb + F_LUT;
  {
    const int n = t, g = n >> 3, qq = (n >> 1) & 3;
    const int pi = 16 * (g >> 2) + 8 * ((g >> 1) & 1) + 2 * qq + (g & 1);
    int a = (n & 1) * 48;
#pragma unroll 2
    for (int c = 0; c < 8; c++) {
      uint32_t w[4];
#pragma unroll
      for (int e = 0; e < 4; e++) { w[e] = lut2(lut, a, a + pi); a += 2 * pi; }
      asm volatile("st.shared.v4.b32 [%0], {%1, %2, %3, %4};" ::"r"(sb + F_C64 + n * 128 + ((c ^ (n & 7)) << 4)), "r"(w[0]), "r"(w[1]), "r"(w[2]), "r"(w[3]) : "memory");
    }
  }
  {
    const int wq = t >> 5, r8 = (t >> 2) & 7, q4 = t & 3;
#pragma unroll 2
    for (int tt = 0; tt < 4; tt++) {
      uint32_t f[4], v[4];
#pragma unroll
      for (int m = 0; m < 4; m++) {
        const int k0 = 16 * tt + 8 * (m >> 1) + 2 * q4, j1 = 8 * wq + r8;
        const int rip = m & 1, ri = tt >> 1;
        const int of = (rip == ri) ? 0 : (rip ? 8 : 24);
        f[m] = lut2(lut, 2 * (j1 * (k0 & 31) + of), 2 * (j1 * ((k0 + 1) & 31) + of));
        const int row = 16 * wq + 8 * (m & 1) + r8;
        const int rp2 = wq >> 1, ri2 = m >> 1;
        const int oi = (rp2 == ri2) ? 0 : (rp2 ? 24 : 8);
        const int jj = 8 * tt + 2 * q4;
        v[m] = lut2(lut, 2 * ((row & 31) * jj + oi), 2 * ((row & 31) * (jj + 1) + oi));
      }
      asm volatile("st.shared.v4.b32 [%0], {%1, %2, %3, %4};" ::"r"(sb + F_ATAB + tt * 2048 + t * 16), "r"(f[0]), "r"(f[1]), "r"(f[2]), "r"(f[3]) : "memory");
      asm volatile("st.shared.v4.b32 [%0], {%1, %2, %3, %4};" ::"r"(sb + F_ATAB + 8192 + tt * 2048 + t * 16), "r"(v[0]), "r"(v[1]), "r"(v[2]), "r"(v[3]) : "memory");
    }
  }
}

__device__ __forceinline__ void ti_gen(const Params& P, int fc, int t3, int lane) {
#pragma unroll 1
  for (int i = 0; i < 12; i++) {
    const int dr = 12 * fc + i;
#pragma unroll
    for (int b = 0; b < 3; b++) {
      const int cc = t3 + 96 * b;
      float c, s;
      cs576((float)(dr * col_freq(cc)), c, s);
      if (cc == 0) s = (dr & 1) ? 1.0f : -1.0f;
      reinterpret_cast<uint32_t*>(P.TI)[dr * 288 + cc] = pack2(c, -s);
    }
  }
  __syncwarp();
  if (lane == 0) { fence_async_glb(); red_release(P.flags + FL_TI * 32, 1u); }
}

__device__ __forceinline__ void g2_block(int it, int gp, int& i2, int& n2, int& hw, int& tl) {
  i2 = it < 10 ? it : it == 10 ? 35 : it - 1;
  n2 = i2 < 2 ? 0 : i2 < 2 + NFH ? i2 - 1 : i2 < 2 + 2 * NFH ? i2 - 1 - NFH : i2 >> 1;
  hw = i2 < 2 ? i2 : i2 < 2 + NFH ? 0 : i2 < 2 + 2 * NFH ? 1 : (i2 & 1) ^ (i2 >= 34);
  tl = n2 < 2 ? (gp ^ n2) : (n2 - 2 < (gp & ~1) ? n2 - 2 : n2);
}

__global__ void __launch_bounds__(NTHREADS, 1) mega_kernel(const __grid_constant__ Params P) {
  extern __shared__ __align__(1024) uint8_t smem_raw[];
  const uint32_t sb = smem_u32(smem_raw);
  const int tid = threadIdx.x, warp = __shfl_sync(0xffffffffu, tid >> 5, 0), lane = tid & 31;
  const int cta = blockIdx.x < NCTA - NG ? blockIdx.x + NG : blockIdx.x - (NCTA - NG);
  const uint32_t rank = cta & 1;
  const uint32_t c_start = (uint32_t)clock();
  const long long t_start = 0;
  const bool isG = cta < NG;
  const bool hasRows = !isG || cta < 104;
  const int row0 = isG ? 384 + cta * 16 : (cta - NG) * 8, rstep = isG ? 8 : 192;
  const uint32_t side = sb + (isG ? SM_SIDE : F1_STG);
  if (warp == 0) {
   if (elect_one()) {
    if (sb & 1023u) __trap();
    mbar_init(sb + B_XR, 1);
    if (!isG) {
      asm volatile("fence.mbarrier_init.release.cluster;" ::: "memory");
      mbar_expect_tx(sb + B_XR, 18432);
      bulk_ld(side, P.Ax + (size_t)row0 * D_, 9216, sb + B_XR);
      bulk_ld(side + 9216, P.Ax + (size_t)(row0 + 192) * D_, 9216, sb + B_XR);
    }
    for (int i = 0; i < 6; i++) { mbar_init(sb + B_FULL + 8 * i, 1); mbar_init(sb + B_EMPTY + 8 * i, isG ? 16 : 8); }
    mbar_init(sb + B_X, 1); mbar_init(sb + B_X1, 8); mbar_init(sb + B_LFREE, 10);
    for (int i = 0; i < 8; i++) mbar_init(sb + B_P + 8 * i, 1);
    for (int i = 0; i < 6; i++) mbar_init(sb + B_U + 8 * i, 4);
    mbar_init(sb + B_HP, 1);
    mbar_init(sb + B_W, 1); mbar_init(sb + B_AUX, 3);
    asm volatile("fence.mbarrier_init.release.cluster;" ::: "memory");
   }
  } else if (tid == 32 && !isG) {
    for (int i = 0; i < 7; i++) { mbar_init(sb + B3_FULL + 8 * i, 1); mbar_init(sb + B3_EMPTY + 8 * i, 8); }
    for (int i = 0; i < 4; i++) mbar_init(sb + B_F2 + 8 * i, 1);
    mbar_init(sb + B_F2DONE, 2); mbar_init(sb + B_RES3, 1);
  }
  __syncthreads();
  if (isG) cluster_arrive();

  if (warp == 2 && isG && hasRows) {
    if (elect_one()) {
      while ((uint32_t)clock() - c_start < XDLY0 + XDLY1 * (uint32_t)cta) {}
      mbar_expect_tx(sb + B_XR, 18432);
      bulk_ld(side, P.Ax + (size_t)row0 * D_, 18432, sb + B_XR);
    }
    __syncwarp();
  }
  if (tid == 128) STAMP(31);
  const int cl = cta >> 1;
  const int gj = cl / 18, kh = (cl % 18) & 1, gp = ((cl % 18) & ~1) + (int)rank;
  const int fc = cta - NG;

  if (warp < 4) {
    asm volatile("setmaxnreg.dec.sync.aligned.u32 56;");
    if (warp == 0) {
      const unsigned ep1 = ld_epoch(P.epoch, cta);
      uint32_t st = 0, ph = 1;
      if (isG) {
        if (elect_one()) { prefetch_map(&P.tW1); prefetch_map(&P.tH); prefetch_map(&P.tW2); prefetch_map(&P.tU); prefetch_map(&P.tU32); }
        cluster_wait();
        const int ft = gp + 18 * kh;
        uint32_t ready = 0, eb = 0x1f;
#pragma unroll 1
        for (int kb = 0; kb < 32; kb++) {
          const uint32_t sa = sb + st * STAGE_BYTES, fb = sb + B_FULL + 8 * st;
          if (kb >= 4) {
            if (!((ready >> kb) & 1)) ready = poll_mask(P.flags, FL_H, 32, ep1 * 8, -1, 3);
            mbar_wait(sb + B_EMPTY + 8 * st, (eb >> st) & 1, 2);
            if (elect_one()) {
              mbar_expect_tx(fb, STAGE_BYTES);
              tma2d(sa, &P.tW1, ft * 128, kb * 64, fb);
              tma2d(sa + 8192, &P.tW1, ft * 128 + 64, kb * 64, fb);
            }
          }
          eb ^= 1u << st;
          if (!((ready >> kb) & 1)) { ready = poll_mask(P.flags, FL_H, 32, ep1 * 8, kb, 3); if (kb == 0 && lane == 0) STAMP(23); }
          if (elect_one()) {
#pragma unroll
            for (int i = 0; i < 3; i++) tma2d_mc(sa + 16384 + i * 8192 + rank * 4096, &P.tH, gj * 192 + i * 64, kb * 64 + rank * 32, fb);
          }
          __syncwarp();
          st = (st + 1) & 3;
        }
        if (lane == 0) STAMP(8);
        if (gp < 16) {
          uint32_t r0 = 0, r1 = 0;
#pragma unroll 1
          for (int it = 0; it < 36; it++) {
            int i2, n2, hw, tl;
            g2_block(it, gp, i2, n2, hw, tl);
            const int f0 = (18 * kh + tl) * 128 + hw * 64;
            const uint32_t ss = it == 10 ? 4u : st;
            if (it == 10) {
              mbar_wait(sb + B_LFREE, 0, 4);
            } else {
              mbar_wait(sb + B_EMPTY + 8 * st, (eb >> st) & 1, 4);
              eb ^= 1u << st;
            }
            const uint32_t sa = sb + ss * STAGE_BYTES, fb = sb + B_FULL + 8 * ss;
            if (elect_one()) {
              mbar_expect_tx(fb, i2 < 2 ? 16384 : STAGE_BYTES);
              tma2d(sa, &P.tW2, gp * 128, f0, fb);
              tma2d(sa + 8192, &P.tW2, gp * 128 + 64, f0, fb);
            }
            if (i2 >= 2) {
              if (!(((hw ? r1 : r0) >> tl) & 1)) poll_u(P.flags, FL_U + gj * 36 + 18 * kh, 18, ep1, tl, hw, r0, r1);
              if (elect_one()) {
                if (n2 == 1 || it == 10) {
#pragma unroll
                  for (int i = 0; i < 3; i++) tma2d(sa + 16384 + i * 8192, &P.tU, gj * 192 + i * 64, f0, fb);
                } else {
#pragma unroll
                  for (int i = 0; i < 3; i++) tma2d_mc(sa + 16384 + i * 8192 + rank * 4096, &P.tU32, gj * 192 + i * 64, f0 + rank * 32, fb);
                }
              }
            }
            __syncwarp();
            if (it != 10) st = (st + 1) & 3;
          }
        }
      } else {
#pragma unroll 1
        for (int r = 0; r < 2; r++) {
          bar_sync(r ? 14 : 5, 288);
          if (lane == 0) {
            TGET(t17);
            fence_async_glb(); red_release(P.flags + (FL_H + ((row0 + 192 * r) >> 6)) * 32, 1u);
            if (r) mbar_arrive(sb + B_HP);
            if (r == 0) { STAMP(22); TPUT(17, t17); } else STAMP(32);
          }
        }
        if (elect_one()) {
          prefetch_map(&P.tXB); prefetch_map(&P.tX1c); prefetch_map(&P.tZT); prefetch_map(&P.tTI);
          {
            const int part = (fc & 2) ? S_ : 0;
#pragma unroll 1
            for (int sblk = fc >> 2; sblk < 16; sblk += 6) {
              wait_flag(P.flags, FL_XB + sblk, ep1 * 16, 7);
#pragma unroll 1
              for (int kb = 0; kb < 5; kb++) {
                const uint32_t fb = sb + B_FULL + 8 * st;
                mbar_wait(sb + B_EMPTY + 8 * st, ph, 8);
                mbar_expect_tx(fb, 16384);
                tma2d(sb + F1_RING + st * 16384, &P.tXB, kb * 64, part + sblk * 128, fb);
                if (++st == 6) { st = 0; ph ^= 1; }
              }
            }
          }
          STAMP(8);
          wait_flag(P.flags, FL_X1, ep1 * 48, 9);
#pragma unroll 1
          for (int b = 0; b < 2; b++)
#pragma unroll 1
            for (int w = 0; w < 2; w++) {
              const uint32_t bar = sb + B_F2 + 8 * (w * 2 + b);
              mbar_expect_tx(bar, 24576);
              for (int c = 0; c < 3; c++) {
                const int cc = w * 144 + fc * 6 + b * 3 + c;
                tma3d(sb + w * 65536 + (b * 3 + c) * 8192, &P.tX1c, 0, 0, 2 * cc, bar);
              }
            }
          STAMP(9);
          wait_flag(P.flags, FL_TI, ep1 * 72, 6);
          mbar_wait(sb + B_F2DONE, 0, 24);
          mbar_expect_tx(sb + B_RES3, 110592);
#pragma unroll 1
          for (int kb = 0; kb < 9; kb++) tma2d(sb + kb * 12288, &P.tTI, kb * 64, (fc % 3) * 96, sb + B_RES3);
          wait_flag(P.flags, FL_Z, ep1 * 48, 10);
          STAMP(10);
          st = 0; ph = 1;
#pragma unroll 1
          for (int it = 0; it < 2; it++) {
            const int sblk = fc / 3 + 8 * it;
#pragma unroll 1
            for (int kb = 0; kb < 9; kb++) {
              const uint32_t sa = sb + F3_RING + st * 16384, fb = sb + B3_FULL + 8 * st;
              mbar_wait(sb + B3_EMPTY + 8 * st, ph, 11);
              mbar_expect_tx(fb, 16384);
              tma2d(sa, &P.tZT, sblk * 128, kb * 64, fb);
              tma2d(sa + 8192, &P.tZT, sblk * 128 + 64, kb * 64, fb);
              if (++st == 7) { st = 0; ph ^= 1; }
            }
          }
        }
        __syncwarp();
      }
    } else {
      if (isG && warp == 3 && elect_one()) {
        const int ft = gp + 18 * kh;
#pragma unroll 1
        for (int s = 0; s < 4; s++) {
          const uint32_t tgo = s == 0 ? W1T0 : W1T1 + W1DT * (uint32_t)(s - 1);
          while ((uint32_t)clock() - c_start < tgo) {}
          mbar_expect_tx(sb + B_FULL + 8 * s, STAGE_BYTES);
          tma2d(sb + s * STAGE_BYTES, &P.tW1, ft * 128, s * 64, sb + B_FULL + 8 * s);
          tma2d(sb + s * STAGE_BYTES + 8192, &P.tW1, ft * 128 + 64, s * 64, sb + B_FULL + 8 * s);
        }
      }
      __syncwarp();
      if (hasRows) {
        bar_sync(11, 352);
        if (warp == 2 && elect_one()) {
          TGET(t21);
          if (isG) {
            const uint32_t dly = HGATE + HDT * (uint32_t)cta;
            while ((uint32_t)clock() - c_start < dly) {}
            bulk_st(P.h + (size_t)row0 * D_, side, 18432);
          } else {
            mbar_wait(sb + B_HP, 0, 35);
          }
          const uint32_t xbs = sb + (isG ? SM_STG : F_XBS);
#pragma unroll 1
          for (int i = 0; i < 4; i++)
            bulk_st(P.xb + (size_t)((i >> 1) * S_ + row0 + (i & 1) * rstep) * 320, xbs + i * 5120, 5120);
          bulk_commit();
          bulk_wait0();
          TGET(t34);
          FENCE_AFTER_BULK();
          fence_gpu();
          if (isG) {
            red_relaxed(P.flags + (FL_H + (row0 >> 6)) * 32, 2u);
            red_relaxed(P.flags + (FL_XB + (row0 >> 7)) * 32, 2u);
          } else {
            red_relaxed(P.flags + (FL_XB + (row0 >> 7)) * 32, 1u);
            red_relaxed(P.flags + (FL_XB + ((row0 + 192) >> 7)) * 32, 1u);
          }
          STAMP(35);
          TPUT(21, t21); TPUT(34, t34);
        }
      }
      if (cta < 128) {
        if (warp == 2 && elect_one()) {
          const int j0 = 64 * (cta >> 2) + 8 * (cta & 3);
          mbar_expect_tx(sb + B_W, 4 * 4624);
          bulk_ld(side, P.Wr + (size_t)j0 * DF_, 4624, sb + B_W);
          bulk_ld(side + 4624, P.Wr + (size_t)(j0 + 32) * DF_, 4624, sb + B_W);
          bulk_ld(side + 9248, P.Wi + (size_t)j0 * DF_, 4624, sb + B_W);
          bulk_ld(side + 13872, P.Wi + (size_t)(j0 + 32) * DF_, 4624, sb + B_W);
        }
        __syncwarp();
        w_job(P, sb, side, cta, tid - 32, lane);
      } else if (lane == 0) {
        mbar_arrive(sb + B_AUX);
      }
      if (!isG) {
        ti_gen(P, fc, tid - 32, lane);
        if (warp == 1) {
#pragma unroll 1
          for (int it = 0; it < 2; it++) {
            bar_sync(7, 288);
            if (lane == 0) { fence_async_glb(); red_release(P.flags + (FL_A + fc / 3 + 8 * it) * 32, 1u); }
            __syncwarp();
          }
        }
      }
      if (lane == 0 && warp == 3) STAMP(11);
      if (isG) cluster_wait();
      if (warp == 3 && isG && gp < 16) {
        const uint4* const src = P.part + (size_t)((gj * 32 + kh * 16 + gp) ^ 16) * 2048;
        bar_sync(10, 160);
        if (elect_one()) {
          const uint32_t tg = (uint32_t)clock();
#pragma unroll 1
          for (int hf = 0; hf < 2; hf++) {
            while ((uint32_t)clock() - tg < (hf ? GDLY2 : GDLY)) {}
#pragma unroll 1
            for (int w = 0; w < 4; w++) {
              mbar_expect_tx(sb + B_P + hf * 32 + 8 * w, 4096);
              bulk_ld(sb + (hf ? X_INB : X_INA) + w * 4096, src + w * 512 + hf * 256, 4096, sb + B_P + hf * 32 + 8 * w);
            }
          }
        }
        __syncwarp();
      }
      if (warp == 2 && isG) {
        if (elect_one()) {
          const int ft = gp + 18 * kh;
#pragma unroll 1
          for (int i = 0; i < 3; i++) {
            mbar_wait(sb + B_U + 24 + 8 * i, 0, 32);
            tma2d_st(&P.tU, sb + SM_STG + 24576 + i * 8192, gj * 192 + i * 64, ft * 128 + 64);
          }
          bulk_commit();
          bulk_wait0();
          TGET(t38);
          mbar_arrive(sb + B_LFREE);
          FENCE_AFTER_BULK();
          red_release(P.flags + (FL_U + gj * 36 + ft) * 32 + 1, 1u);
          STAMP(39);
          TPUT(38, t38);
        }
      }
      if (warp == 1 && isG) {
        const unsigned ep1 = ld_epoch(P.epoch, cta);
        if (elect_one()) {
          const int ft = gp + 18 * kh;
#pragma unroll 1
          for (int i = 0; i < 3; i++) {
            mbar_wait(sb + B_U + 8 * i, 0, 33);
            tma2d_st(&P.tU, sb + SM_STG + i * 8192, gj * 192 + i * 64, ft * 128);
          }
          bulk_commit();
          TGET(t29);
          bulk_wait0();
          TGET(t30);
          mbar_arrive(sb + B_LFREE);
          FENCE_AFTER_BULK();
          red_release(P.flags + (FL_U + gj * 36 + ft) * 32, 1u);
          STAMP(15);
          TPUT(29, t29); TPUT(30, t30);
          if (gp < 16) {
            wait_flag(P.flags, FL_XB + gp, ep1 * 16, 16);
            mbar_wait(sb + B_AUX, 0, 28);
            mbar_expect_tx(sb + B_X, 24576 + 512);
            bulk_ld(sb + X_GATE, P.gate + gp * 128, 512, sb + B_X);
            wait_flag(P.flags, FL_A + gp, ep1 * 3, 17);
            mbar_wait(sb + B_X1, 0, 12);
            bulk_ld(sb + 3 * STAGE_BYTES, P.afrag + (size_t)(((gp * 2 + kh) * 6 + 2 * gj) * 6) * 128, 24576, sb + B_X);
          }
        }
      }
    }
  } else {
    asm volatile("setmaxnreg.inc.sync.aligned.u32 224;");
    const int cw = warp - 4;
    const int wg = cw >> 2, wq = cw & 3;
    const int ct = tid - 128;
    const int q4 = lane & 3, r8 = lane >> 2;
    const unsigned ep0 = ld_epoch_raw(P.epoch, cta);
    if (hasRows) {
      uint32_t gl[5], gh[5];
      const uint32_t* gw = reinterpret_cast<const uint32_t*>(P.gw) + lane;
#pragma unroll
      for (int i = 0; i < 5; i++) { gl[i] = (i < 4 || lane < 16) ? __ldg(gw + 32 * i) : 0u; gh[i] = (i < 4 || lane < 16) ? __ldg(gw + 144 + 32 * i) : 0u; }
      if (ct == 0) STAMP(16);
      mbar_wait(sb + B_XR, 0, 27);
      if (ct == 0) STAMP(33);
      if (isG) {
        uint32_t lo[2][5], hi[2][5];
        pair_load(side + cw * 2304, lane, lo, hi);
        ln_pair(reinterpret_cast<uint32_t*>(smem_raw + SM_SIDE) + cw * 576, lane, lo, hi);
        if (ct == 0) STAMP(18);
        xb_pair_regs(P, row0 + cw * 2, reinterpret_cast<uint32_t*>(smem_raw + SM_STG) + cw * 320, 2560u, lane, lo, hi, gl, gh);
      } else {
#pragma unroll 1
        for (int r = 0; r < 2; r++) {
          uint32_t lo[5], hi[5];
          row_load(side + (r * 8 + cw) * 1152, lane, lo, hi);
          ln_row(reinterpret_cast<uint32_t*>(P.h + (size_t)(row0 + r * 192 + cw) * D_) + lane, lane, lo, hi);
          if (ct == 0 && r == 0) STAMP(18);
          bar_arrive(r ? 14 : 5, 288);
        }
        xb_pair(P.gate + row0 + cw, 192, side + cw * 1152, reinterpret_cast<uint32_t*>(smem_raw + F_XBS) + cw * 160, lane, gl, gh);
      }
      fence_async_smem();
      bar_arrive(11, 352);
    }
    if (ep0 == 0xFFFFFFF0u && S_ == 2048 && blockIdx.x > NCTA) {
#pragma unroll
      for (int i = 0; i < PADN; i++) asm volatile("nanosleep.u32 7;");
    }
    if (isG) cluster_wait();
    if (ct == 0) STAMP(0);
    unsigned ep1;
    asm volatile("add.u32 %0, %1, 1;" : "=r"(ep1) : "r"(ep0));
    uint32_t st = 0, ph = 0;
    if (isG) {
      uint32_t fpar = 0;
      const uint32_t rel = mapa(sb + B_EMPTY, lane == 0 ? rank : rank ^ 1);
      const int ft = gp + 18 * kh;
      const uint32_t bias0 = dup_bf(P.b1 + ft * 128 + wg * 64 + wq * 16 + r8), bias1 = dup_bf(P.b1 + ft * 128 + wg * 64 + wq * 16 + r8 + 8);
      float acc[96];
      const uint64_t dA0 = mkdesc(sb + wg * 8192, 8192, 1024), dB0 = mkdesc(sb + 16384, 8192, 1024);
      uint32_t prev = 0;
#pragma unroll 1
      for (int kb = 0; kb < 28; kb++) {
        mbar_wait(sb + B_FULL + 8 * st, (fpar >> st) & 1, 13);
        fpar ^= 1u << st;
        if (kb == 0 && ct == 0) STAMP(1);
        if (ct == 0 && (kb == 1 || kb == 2 || kb == 4 || kb == 8 || kb == 16)) STAMP(kb == 1 ? 9 : kb == 2 ? 10 : kb == 4 ? 12 : kb == 8 ? 13 : 14);
        const uint64_t so = (uint64_t)(st * (STAGE_BYTES >> 4));
        wg_fence();
#pragma unroll
        for (int kk = 0; kk < 4; kk++) wg_ss_n192<1, 1>(acc, dA0 + so + kk * 128, dB0 + so + kk * 128, (kb | kk) != 0);
        wg_commit();
        if (kb > 0) { wg_wait<1>(); if (lane < 2) mbar_arrive_remote(rel + 8 * prev); }
        prev = st;
        st = (st + 1) & 3;
      }
      if (wg == 1) {
        wg_wait<0>();
        if (lane < 2) mbar_arrive_remote(rel + 8 * prev);
        bar_sync(6, 256);
      }
#pragma unroll 1
      for (int kb = 28; kb < 32; kb++) {
        if (wg == 0 && kb == SKEW_KB) bar_arrive(6, 256);
        mbar_wait(sb + B_FULL + 8 * st, (fpar >> st) & 1, 13);
        fpar ^= 1u << st;
        const uint64_t so = (uint64_t)(st * (STAGE_BYTES >> 4));
        wg_fence();
#pragma unroll
        for (int kk = 0; kk < 4; kk++) wg_ss_n192<1, 1>(acc, dA0 + so + kk * 128, dB0 + so + kk * 128, 1);
        wg_commit();
        wg_wait<1>();
        if (lane < 2 && (kb == 28 ? wg == 0 : gp < 16)) mbar_arrive_remote(rel + 8 * prev);
        prev = st;
        st = (st + 1) & 3;
      }
      wg_wait<0>();
      if (lane < 2 && gp < 16) mbar_arrive_remote(rel + 8 * prev);
      if (ct == 0) STAMP(2);

      {
        const int jm = lane >> 3, i8 = lane & 7;
        const uint32_t row = wq * 16 + (jm & 1) * 8 + i8;
        uint32_t base = sb + SM_STG + wg * 24576 + row * 128;
        uint32_t xp[48];
#pragma unroll
        for (int k = 0; k < 48; k++) xp[k] = badd2(pack2(acc[2 * k], acc[2 * k + 1]), (k & 1) ? bias1 : bias0);
#pragma unroll 1
        for (int b = 0; b < 3; b++) {
#pragma unroll
          for (int g = 0; g < 4; g++) {
            uint32_t r[4];
#pragma unroll
            for (int m = 0; m < 4; m++) r[m] = pack2(gelu_tanh(bf_lo(xp[4 * g + m])), gelu_tanh(bf_hi(xp[4 * g + m])));
            stsm4(base + (((2 * g + (jm >> 1)) ^ i8) << 4), r[0], r[1], r[2], r[3]);
          }
          fence_async_smem();
          __syncwarp();
          if (lane == 0) mbar_arrive(sb + B_U + wg * 24 + b * 8);
#pragma unroll
          for (int k = 0; k < 32; k++) xp[k] = xp[k + 16];
          base += 8192;
        }
      }
      if (ct == 0) STAMP(3);
      if (ct == 128) STAMP(41);
      if (gp < 16) {
        if (wg == 0) bar_sync(1, 128); else bar_sync(9, 256);
        const uint64_t dS0 = mkdesc(sb + SM_STG, 8192, 1024);
        const bool recv = wg == kh;
        const int frow = kh * 64 + wq * 16 + r8;
        const int slot = gj * 32 + kh * 16 + gp;
        uint4* const xdst = P.part + (size_t)slot * 2048 + wq * 512;
        const uint32_t c0 = dup_bf(P.b2 + gp * 128 + frow), c1 = dup_bf(P.b2 + gp * 128 + frow + 8);
#pragma unroll 1
        for (int i2 = 0; i2 < 32; i2++) {
          mbar_wait(sb + B_FULL + 8 * st, (fpar >> st) & 1, 14);
          fpar ^= 1u << st;
          if (i2 == 1 && wg == 0) bar_sync(9, 256);
          const uint64_t so = (uint64_t)(st * (STAGE_BYTES >> 4));
          const uint64_t db = i2 < 2 ? dS0 + (uint64_t)(i2 * (24576 >> 4)) : dB0 + so;
          wg_fence();
#pragma unroll
          for (int kk = 0; kk < 4; kk++) wg_ss_n192<1, 1>(acc, dA0 + so + kk * 128, db + kk * 128, (i2 | kk) != 0);
          wg_commit();
          if (i2 > 0) {
            wg_wait<1>();
            if (lane < 2) mbar_arrive_remote(rel + 8 * prev);
            if (lane == 0 && i2 == 2) mbar_arrive(sb + B_LFREE);
          }
          if (!recv && (unsigned)(i2 - 8) < 16u) {
            if (i2 == 8) {
              mbar_wait(sb + B_AUX, 0, 28);
              asm volatile("st.shared.v4.b32 [%0], {%1, %1, %1, %1};" ::"r"(sb + X_PAT + wq * 512 + lane * 16), "r"(~ep1 << 31) : "memory");
              fence_async_smem();
              __syncwarp();
            }
            if (elect_one()) { bulk_st(xdst + (i2 - 8) * 32, sb + X_PAT + wq * 512, 512); bulk_commit(); }
          }
          if (!recv && i2 == 29) {
            if (elect_one()) { bulk_wait0(); fence_async_glb(); }
            __syncwarp();
          }
          prev = st;
          st = (st + 1) & 3;
        }
        st = 4;
        if (recv) {
          wg_wait<0>();
          if (lane == 0) mbar_arrive(sb + B_X1);
          if ((ct & 127) == 0) STAMP(43);
          bar_sync(6, 256);
        }
#pragma unroll 1
        for (int i2 = 32; i2 < 36; i2++) {
          mbar_wait(sb + B_FULL + 8 * st, (fpar >> st) & 1, 14);
          fpar ^= 1u << st;
          const uint64_t so = (uint64_t)(st * (STAGE_BYTES >> 4));
          wg_fence();
#pragma unroll
          for (int kk = 0; kk < 4; kk++) wg_ss_n192<1, 1>(acc, dA0 + so + kk * 128, dB0 + so + kk * 128, 1);
          wg_commit();
          wg_wait<1>();
          if (!recv && i2 == 32 && lane == 0) mbar_arrive(sb + B_X1);
          if (!recv && (ct & 127) == 0) STAMP(i2 == 32 ? 17 : i2 == 33 ? 19 : i2 == 34 ? 20 : 22);
          st = st == 4 ? 0 : st + 1;
        }
        const uint32_t tag = ep1 & 1u;
        const uint4* const src = P.part + (size_t)(slot ^ 16) * 2048 + wq * 512;
        wg_wait<0>();
        if (!recv) {
          if ((ct & 127) == 0) STAMP(4);
          bar_arrive(13, 256);
          bar_arrive(6, 256);
#pragma unroll
          for (int u = 0; u < 16; u++)
            st_part(xdst + u * 32 + lane, acc[6 * u], acc[6 * u + 1], acc[6 * u + 2], acc[6 * u + 3], acc[6 * u + 4], acc[6 * u + 5], tag);
          bar_arrive(10, 160);
          if ((ct & 127) == 0) STAMP(44);
        } else {
          if ((ct & 127) == 0) STAMP(42);
#pragma unroll
          for (int j = 0; j < 12; j++)
            asm volatile("st.shared.v4.f32 [%0], {%1, %2, %3, %4};" ::"r"(sb + X_HAND + j * 2048 + (ct & 127) * 16),
                         "f"(acc[48 + 4 * j]), "f"(acc[49 + 4 * j]), "f"(acc[50 + 4 * j]), "f"(acc[51 + 4 * j]) : "memory");
          bar_arrive(12, 256);
          bar_sync(13, 256);
        }
        {
          const uint32_t hf = recv ? 0u : 1u;
          if (!recv) {
            if ((ct & 127) == 0) STAMP(45);
            bar_sync(12, 256);
#pragma unroll
            for (int j = 0; j < 12; j++)
              asm volatile("ld.shared.v4.f32 {%0, %1, %2, %3}, [%4];" : "=f"(acc[4 * j]), "=f"(acc[4 * j + 1]), "=f"(acc[4 * j + 2]), "=f"(acc[4 * j + 3])
                           : "r"(sb + X_HAND + j * 2048 + (ct & 127) * 16));
          }
          mbar_wait(sb + B_X, 0, 18);
          if (recv && (ct & 127) == 0) STAMP(5);
          float gf0, gf1;
          asm volatile("ld.shared.f32 %0, [%1];" : "=f"(gf0) : "r"(sb + X_GATE + frow * 4));
          asm volatile("ld.shared.f32 %0, [%1];" : "=f"(gf1) : "r"(sb + X_GATE + frow * 4 + 32));
          const uint32_t g0 = pack2(gf0, gf0), g1 = pack2(gf1, gf1), og0 = pack2(1.0f - gf0, 1.0f - gf0), og1 = pack2(1.0f - gf1, 1.0f - gf1);
          const int jm = lane >> 3, i8 = lane & 7;
          const uint32_t row = wq * 16 + (jm & 1) * 8 + i8;
          const uint32_t obox = sb + X_OUT + hf * 12288;
          const uint32_t want = tag << 31;
          const uint32_t pbar = sb + B_P + hf * 32 + 8 * wq, inb = sb + (recv ? X_INA : X_INB) + wq * 4096;
          uint32_t pz[32];
#pragma unroll 1
          for (uint32_t it = 0;; it++) {
            mbar_wait(pbar, it & 1, 31);
            uint32_t bad = 0;
#pragma unroll
            for (int h = 0; h < 8; h++) {
              asm volatile("ld.shared.v4.b32 {%0, %1, %2, %3}, [%4];" : "=r"(pz[4 * h]), "=r"(pz[4 * h + 1]), "=r"(pz[4 * h + 2]), "=r"(pz[4 * h + 3])
                           : "r"(inb + h * 512 + lane * 16) : "memory");
              bad |= (pz[4 * h + 1] ^ want) | (pz[4 * h + 3] ^ want);
            }
            if (!__any_sync(0xffffffffu, (int)bad < 0)) break;
            if (it > 0x10000u) __trap();
            if (elect_one()) { mbar_expect_tx(pbar, 4096); bulk_ld(inb, src + hf * 256, 4096, pbar); }
          }
          if (recv && (ct & 127) == 0) STAMP(46);
#pragma unroll
          for (int i = 0; i < 6; i++) {
            uint32_t aw[4];
            asm volatile("ld.shared.v4.b32 {%0, %1, %2, %3}, [%4];" : "=r"(aw[0]), "=r"(aw[1]), "=r"(aw[2]), "=r"(aw[3])
                         : "r"(sb + 3 * STAGE_BYTES + (hf * 6 + i) * 2048 + (ct & 127) * 16));
            float v[8];
#pragma unroll
            for (int e = 0; e < 8; e++) {
              const int o = 8 * i + e, t = o / 3, c = o % 3;
              const uint32_t lo = pz[2 * t], hi = pz[2 * t + 1];
              const uint32_t q = c == 0 ? lo << 11 : c == 1 ? (__funnelshift_r(lo, hi, 10) & 0xFFFFF800u) : ((hi << 1) & 0xFFFFF800u);
              v[e] = acc[o] + __uint_as_float(q);
            }
            uint32_t r[4];
#pragma unroll
            for (int m = 0; m < 4; m++) {
              const uint32_t bb = badd2(pack2(v[2 * m], v[2 * m + 1]), (m & 1) ? c1 : c0);
              r[m] = badd2(bmul2((m & 1) ? g1 : g0, aw[m]), bmul2((m & 1) ? og1 : og0, bb));
            }
            const uint32_t grp = 2 * (i & 1) + (jm >> 1);
            stsm4(obox + (i >> 1) * 4096 + row * 64 + ((grp ^ ((row >> 1) & 3)) << 4), r[0], r[1], r[2], r[3]);
            if (i & 1) {
              fence_async_smem();
              bar_sync(2 + wg, 128);
              if (wq == 0 && elect_one()) {
                tma2d_st(&P.tOut, obox + (i >> 1) * 4096, gj * 192 + hf * 96 + (i >> 1) * 32, gp * 128 + kh * 64);
                bulk_commit();
              }
            }
          }
        }
        if (recv && (ct & 127) == 0) STAMP(7);
        if (wq == 0 && elect_one()) bulk_wait0_read();
        if (recv && (ct & 127) == 0) STAMP(6);
        if (!recv && (ct & 127) == 0) STAMP(40);
      }
      if (ct == 0) P.epoch[cta * 32] = ep1;
    } else {
      b1_gen(sb, fc & 3, cw, lane);
      fence_async_smem();
      bar_sync(4, 256);
      if (ct == 0) STAMP(1);
      const int jm = lane >> 3, i8 = lane & 7;
      {
        const uint64_t dA0 = mkdesc(sb + F1_RING + wg * 8192, 16, 1024), dB0 = mkdesc(sb, 16, 1024);
        float acc[72];
        bool first = true;
#pragma unroll 1
        for (int sblk = fc >> 2; sblk < 16; sblk += 6) {
          uint32_t prev = 0;
#pragma unroll 1
          for (int kb = 0; kb < 4; kb++) {
            mbar_wait(sb + B_FULL + 8 * st, ph, 19);
            if (ct == 0 && sblk >= 6 && sblk < 12 && kb == 0) STAMP(29);
            const uint64_t ao = dA0 + (uint64_t)(st * 1024), bo = dB0 + (uint64_t)(kb * 1152);
            wg_fence();
            wg_ss_n144<0, 0>(acc, ao, bo, kb != 0);
            wg_ss_n144<0, 0>(acc, ao + 2, bo + 2, 1);
            wg_ss_n144<0, 0>(acc, ao + 4, bo + 4, 1);
            wg_ss_n144<0, 0>(acc, ao + 6, bo + 6, 1);
            wg_commit();
            if (kb > 0) { wg_wait<1>(); if (lane == 0) mbar_arrive(sb + B_EMPTY + 8 * prev); }
            prev = st;
            if (++st == 6) { st = 0; ph ^= 1; }
          }
          {
            mbar_wait(sb + B_FULL + 8 * st, ph, 19);
            if (ct == 0 && sblk >= 6 && sblk < 12) STAMP(30);
            const uint64_t ao = dA0 + (uint64_t)(st * 1024), bo = dB0 + (uint64_t)(4 * 1152);
            wg_fence();
            wg_ss_n144<0, 0>(acc, ao, bo, 1);
            wg_ss_n144<0, 0>(acc, ao + 2, bo + 2, 1);
            wg_commit();
            wg_wait<1>();
            if (lane == 0) mbar_arrive(sb + B_EMPTY + 8 * prev);
            prev = st;
            if (++st == 6) { st = 0; ph ^= 1; }
          }
          wg_wait<0>();
          if (lane == 0) mbar_arrive(sb + B_EMPTY + 8 * prev);
          if (first) { mbar_wait(sb + B_AUX, 0, 20); first = false; }
          if (wq == 0 && elect_one()) bulk_wait0_read();
          bar_sync(2 + wg, 128);
          const uint32_t base = sb + F1_STG + wg * 18432;
#pragma unroll
          for (int G = 0; G < 18; G += 2) {
            const uint32_t row = 8 * (G + (jm >> 1)) + i8;
            stsm4t(base + row * 128 + (((2 * wq + (jm & 1)) ^ i8) << 4), pack2(acc[4 * G], acc[4 * G + 1]), pack2(acc[4 * G + 2], acc[4 * G + 3]),
                   pack2(acc[4 * G + 4], acc[4 * G + 5]), pack2(acc[4 * G + 6], acc[4 * G + 7]));
          }
          fence_async_smem();
          bar_sync(2 + wg, 128);
          if (wq == 0 && elect_one()) { tma2d_st(&P.tX1s, base, sblk * 128 + wg * 64, (fc & 3) * 144); bulk_commit(); }
          if (ct == 0) STAMP(25 + sblk / 6);
        }
        bar_sync(4, 256);
        if (ct >= 64 && ct < 128) {
          asm volatile("st.shared.u16 [%0], %1;" ::"r"(sb + F_LUT + (ct - 64) * 2), "h"((uint16_t)pack2(cos_frac(ct - 64, 64), 0.f)) : "memory");
        }
        if (wq == 0 && elect_one()) { bulk_wait0(); TGET(t24); FENCE_AFTER_BULK(); red_release(P.flags + FL_X1 * 32, 1u); if (ct == 0) TPUT(24, t24); }
        if (wq >= 2) bar_sync(8, 128);
      }
      if (ct == 0) STAMP(2);
      {
        if (wq >= 2) f2_consts(sb, wg * 64 + (ct & 127) - 64);
        const int j1 = 8 * wq + r8;
        const uint32_t atab = sb + F_ATAB + (ct & 127) * 16;
        float twc[16], tws[16];
#pragma unroll
        for (int i = 0; i < 16; i++) {
          const int an = j1 * (8 * (i >> 1) + 2 * q4 + (i & 1));
          twc[i] = cos_frac(an, 2048); tws[i] = sin_frac(an, 2048);
        }
        fence_async_smem();
        if (lane == 0) wait_flag(P.flags, FL_WT, ep1 * 384, 21);
        bar_sync(4, 256);
        const uint64_t dC = mkdesc(sb + F_C64, 16, 1024);
        const uint32_t wbase = sb + wg * 65536;
        const uint32_t strow = (16 * wq + 8 * (jm & 1) + i8) * 128;
        constexpr float SCALE = 2.0f / (2048.0f * 576.0f);
        const uint2* wp = reinterpret_cast<const uint2*>(P.Wt + (size_t)(wg * 144 + fc * 6) * 2048) + q4 * 32 + j1;
        uint2 Wn[8];
#pragma unroll
        for (int G = 0; G < 8; G++) Wn[G] = __ldcg(wp + G * 128);
#pragma unroll 1
        for (int c = 0; c < 6; c++) {
          const uint32_t xbuf = wbase + c * 8192, tbuf = wbase + 49152 + (c & 1) * 8192;
          const int cc = wg * 144 + fc * 6 + c;
          uint2 Wv[8];
#pragma unroll
          for (int G = 0; G < 8; G++) Wv[G] = Wn[G];
          if (c < 5) {
            wp += 1024;
#pragma unroll
            for (int G = 0; G < 8; G++) Wn[G] = __ldcg(wp + G * 128);
          }
          uint32_t A[16];
#pragma unroll
          for (int t = 0; t < 4; t++)
            asm volatile("ld.shared.v4.b32 {%0, %1, %2, %3}, [%4];" : "=r"(A[4 * t]), "=r"(A[4 * t + 1]), "=r"(A[4 * t + 2]), "=r"(A[4 * t + 3]) : "r"(atab + t * 2048));
          if (c == 0 || c == 3) mbar_wait(sb + B_F2 + 8 * (wg * 2 + (c != 0)), 0, 22);
          const bool stm = (ct == 0 && c == 2);
          if (stm) STAMP(5);
          {
            float acc[32];
            const uint64_t dX = mkdesc(xbuf, 8192, 1024);
            wg_fence();
#pragma unroll
            for (int t = 0; t < 4; t++) wg_rs_n64<1>(acc, A[4 * t], A[4 * t + 1], A[4 * t + 2], A[4 * t + 3], dX + t * 128, t != 0);
            wg_commit();
            wg_wait<0>();
#pragma unroll
            for (int G = 0; G < 8; G++) {
              const float* a = &acc[4 * G];
              const float c0 = twc[2 * G], s0 = tws[2 * G], c1 = twc[2 * G + 1], s1 = tws[2 * G + 1];
              A[4 * (G >> 1) + 2 * (G & 1)] = pack2(a[0] * c0 + a[2] * s0, a[1] * c1 + a[3] * s1);
              A[4 * (G >> 1) + 2 * (G & 1) + 1] = pack2(a[2] * c0 - a[0] * s0, a[3] * c1 - a[1] * s1);
            }
          }
          float acc[64];
          wg_fence();
#pragma unroll
          for (int t = 0; t < 4; t++) wg_rs_n128<0>(acc, A[4 * t], A[4 * t + 1], A[4 * t + 2], A[4 * t + 3], dC + t * 2, t != 0);
          wg_commit();
          wg_wait<0>();
          if (cc == 0) {
            const uint32_t scr = sb + 131072;
#pragma unroll
            for (int g = 0; g < 16; g++) {
              const int j = j1 + 32 * (8 * (g >> 1) + 2 * q4 + (g & 1));
              asm volatile("st.shared.v2.f32 [%0], {%1, %2};" ::"r"(scr + j * 8), "f"(acc[4 * g] + acc[4 * g + 3]), "f"(acc[4 * g + 2] - acc[4 * g + 1]) : "memory");
            }
            bar_sync(2 + wg, 128);
#pragma unroll
            for (int G = 0; G < 8; G++) {
              float pr[2], pi[2];
#pragma unroll
              for (int e = 0; e < 2; e++) {
                const int g = 2 * G + e;
                const int j = j1 + 32 * (8 * G + 2 * q4 + e), jn = (S_ - j) & (S_ - 1);
                float nr, ni;
                asm volatile("ld.shared.v2.f32 {%0, %1}, [%2];" : "=f"(nr), "=f"(ni) : "r"(scr + jn * 8));
                const uint2 wa = __ldcg(P.W0 + j), wb = __ldcg(P.W0 + jn);
                const float h0r = bf_lo(wa.x) + bf_lo(wb.x), h0i = bf_hi(wa.x) - bf_hi(wb.x), h1r = bf_lo(wa.y) + bf_lo(wb.y), h1i = bf_hi(wa.y) - bf_hi(wb.y);
                const float4 uv = make_float4(0.125f * (h0r + h1r), 0.125f * (h0i + h1i), 0.125f * (h0r - h1r), 0.125f * (h0i - h1i));
                const float xr = acc[4 * g] + acc[4 * g + 3], xi = acc[4 * g + 2] - acc[4 * g + 1];
                pr[e] = uv.x * xr - uv.y * xi + uv.z * nr + uv.w * ni;
                pi[e] = uv.x * xi + uv.y * xr + uv.w * nr - uv.z * ni;
              }
              A[4 * (G >> 1) + 2 * (G & 1)] = pack2(pr[0], pr[1]);
              A[4 * (G >> 1) + 2 * (G & 1) + 1] = pack2(pi[0], pi[1]);
            }
          } else {
#pragma unroll
            for (int G = 0; G < 8; G++) {
              const float* a = &acc[8 * G];
              const float x0r = a[0] + a[3], x0i = a[2] - a[1], x1r = a[4] + a[7], x1i = a[6] - a[5];
              const float w0r = bf_lo(Wv[G].x), w0i = bf_hi(Wv[G].x), w1r = bf_lo(Wv[G].y), w1i = bf_hi(Wv[G].y);
              A[4 * (G >> 1) + 2 * (G & 1)] = pack2(x0r * w0r - x0i * w0i, x1r * w1r - x1i * w1i);
              A[4 * (G >> 1) + 2 * (G & 1) + 1] = pack2(x0r * w0i + x0i * w0r, x1r * w1i + x1i * w1r);
            }
          }
          wg_fence();
#pragma unroll
          for (int t = 0; t < 4; t++) wg_rs_n128<0>(acc, A[4 * t], A[4 * t + 1], A[4 * t + 2], A[4 * t + 3], dC + t * 2, t != 0);
          wg_commit();
#pragma unroll
          for (int t = 0; t < 4; t++)
            asm volatile("ld.shared.v4.b32 {%0, %1, %2, %3}, [%4];" : "=r"(Wv[2 * t].x), "=r"(Wv[2 * t].y), "=r"(Wv[2 * t + 1].x), "=r"(Wv[2 * t + 1].y) : "r"(atab + 8192 + t * 2048));
          wg_wait<0>();
#pragma unroll
          for (int G = 0; G < 8; G += 2) {
            uint32_t r[4];
#pragma unroll
            for (int h = 0; h < 2; h++) {
              const float* a = &acc[8 * (G + h)];
              const float v0r = (a[0] - a[3]) * SCALE, v0i = (a[2] + a[1]) * SCALE, v1r = (a[4] - a[7]) * SCALE, v1i = (a[6] + a[5]) * SCALE;
              const float c0 = twc[2 * (G + h)], s0 = tws[2 * (G + h)], c1 = twc[2 * (G + h) + 1], s1 = tws[2 * (G + h) + 1];
              r[2 * h] = pack2(v0r * c0 - v0i * s0, v1r * c1 - v1i * s1);
              r[2 * h + 1] = pack2(v0i * c0 + v0r * s0, v1i * c1 + v1r * s1);
            }
            stsm4(tbuf + strow + (((G + (jm >> 1)) ^ i8) << 4), r[0], r[1], r[2], r[3]);
          }
          fence_async_smem();
          bar_sync(2 + wg, 128);
          if (c > 0 && wq == 0 && elect_one()) { tma3d_st(&P.tZc, xbuf - 8192, 0, 0, 2 * (cc - 1)); bulk_commit(); }
          {
            float ac2[32];
            const uint64_t dT = mkdesc(tbuf, 8192, 1024);
            wg_fence();
#pragma unroll
            for (int t = 0; t < 4; t++) wg_rs_n64<1>(ac2, Wv[2 * t].x, Wv[2 * t].y, Wv[2 * t + 1].x, Wv[2 * t + 1].y, dT + t * 128, t != 0);
            wg_commit();
            wg_wait<0>();
#pragma unroll
            for (int G = 0; G < 8; G += 2) {
              const float* a = &ac2[4 * G];
              stsm4(xbuf + strow + (((G + (jm >> 1)) ^ i8) << 4), pack2(a[0], a[1]), pack2(a[2], a[3]), pack2(a[4], a[5]), pack2(a[6], a[7]));
            }
          }
          if (stm) STAMP(7);
        }
        fence_async_smem();
        bar_sync(2 + wg, 128);
        if (wq == 0 && elect_one()) {
          tma3d_st(&P.tZc, wbase + 5 * 8192, 0, 0, 2 * (wg * 144 + fc * 6 + 5));
          TGET(t19);
          bulk_commit(); bulk_wait0();
          TGET(t23);
          FENCE_AFTER_BULK(); red_release(P.flags + FL_Z * 32, 1u);
          if (ct == 0) { TPUT(19, t19); TPUT(23, t23); }
          mbar_arrive(sb + B_F2DONE);
        }
      }
      if (ct == 0) STAMP(3);
      {
        const uint64_t dA0 = mkdesc(sb + F3_RING + wg * 8192, 8192, 1024), dB0 = mkdesc(sb, 16, 1024);
        mbar_wait(sb + B_RES3, 0, 25);
        st = 0; ph = 0;
#pragma unroll 1
        for (int it = 0; it < 2; it++) {
          const int sblk = fc / 3 + 8 * it, q = fc % 3;
          float ev[48], od[48];
          uint32_t prev = 0;
#define F3W0
#define F3W1_(KB)
#define F3_STEP(ACC0, ACC1, KB, F0, F1, REL)                                                                                      \
          {                                                                                                                        \
            mbar_wait(sb + B3_FULL + 8 * st, ph, 23);                                                                              \
            F3W1_(KB)                                                                                                              \
            const uint64_t ao = dA0 + (uint64_t)(st * 1024), bo = dB0 + (uint64_t)((KB) * 768);                                    \
            wg_fence();                                                                                                            \
            wg_ss_n96<1, 0>(ACC0, ao, bo, F0);                                                                                     \
            wg_ss_n96<1, 0>(ACC0, ao + 128, bo + 2, 1);                                                                            \
            wg_ss_n96<1, 0>(ACC1, ao + 256, bo + 4, F1);                                                                           \
            wg_ss_n96<1, 0>(ACC1, ao + 384, bo + 6, 1);                                                                            \
            wg_commit();                                                                                                           \
            if (REL) { wg_wait<1>(); if (lane == 0) mbar_arrive(sb + B3_EMPTY + 8 * prev); }                                       \
            prev = st;                                                                                                             \
            if (++st == 7) { st = 0; ph ^= 1; }                                                                                    \
          }
#pragma unroll 1
          for (int kb = 0; kb < 4; kb++) F3_STEP(ev, ev, kb, kb != 0, 1, kb > 0)
          F3_STEP(ev, od, 4, 1, 0, true)
#pragma unroll 1
          for (int kb = 5; kb < 9; kb++) F3_STEP(od, od, kb, 1, 1, true)
          wg_wait<0>();
          if (lane == 0) mbar_arrive(sb + B3_EMPTY + 8 * prev);
#pragma unroll
          for (int i = 0; i < 6; i++) {
            uint4 p, m;
            p.x = pack2(ev[8 * i] + od[8 * i], ev[8 * i + 1] + od[8 * i + 1]); m.x = pack2(ev[8 * i] - od[8 * i], ev[8 * i + 1] - od[8 * i + 1]);
            p.y = pack2(ev[8 * i + 2] + od[8 * i + 2], ev[8 * i + 3] + od[8 * i + 3]); m.y = pack2(ev[8 * i + 2] - od[8 * i + 2], ev[8 * i + 3] - od[8 * i + 3]);
            p.z = pack2(ev[8 * i + 4] + od[8 * i + 4], ev[8 * i + 5] + od[8 * i + 5]); m.z = pack2(ev[8 * i + 4] - od[8 * i + 4], ev[8 * i + 5] - od[8 * i + 5]);
            p.w = pack2(ev[8 * i + 6] + od[8 * i + 6], ev[8 * i + 7] + od[8 * i + 7]); m.w = pack2(ev[8 * i + 6] - od[8 * i + 6], ev[8 * i + 7] - od[8 * i + 7]);
            P.afrag[((size_t)((sblk * 2 + wg) * 6 + q) * 6 + i) * 128 + (ct & 127)] = p;
            P.afrag[((size_t)((sblk * 2 + wg) * 6 + q + 3) * 6 + i) * 128 + (ct & 127)] = m;
          }
          bar_arrive(7, 288);
          if (ct == 0 && it == 0) STAMP(6);
        }
      }
      if (ct == 0) { STAMP(4); P.epoch[cta * 32] = ep1; }
    }
  }
}

typedef CUresult (*EncFn)(CUtensorMap*, CUtensorMapDataType, cuuint32_t, void*, const cuuint64_t*, const cuuint64_t*, const cuuint32_t*,
                          const cuuint32_t*, CUtensorMapInterleave, CUtensorMapSwizzle, CUtensorMapL2promotion, CUtensorMapFloatOOBfill);

void mk2d(EncFn enc, CUtensorMap* m, const void* p, uint64_t inner, uint64_t outer, uint32_t bi, uint32_t bo, CUtensorMapSwizzle sw, uint64_t pitch = 0) {
  cuuint64_t dims[2] = {inner, outer}; cuuint64_t str[1] = {(pitch ? pitch : inner) * 2}; cuuint32_t box[2] = {bi, bo}; cuuint32_t es[2] = {1, 1};
  enc(m, CU_TENSOR_MAP_DATA_TYPE_BFLOAT16, 2, const_cast<void*>(p), dims, str, box, es, CU_TENSOR_MAP_INTERLEAVE_NONE, sw,
      CU_TENSOR_MAP_L2_PROMOTION_L2_256B, CU_TENSOR_MAP_FLOAT_OOB_FILL_NONE);
}
void mk3d(EncFn enc, CUtensorMap* m, const void* p) {
  cuuint64_t dims[3] = {64, 32, 576}; cuuint64_t str[2] = {128, 4096}; cuuint32_t box[3] = {64, 32, 2}; cuuint32_t es[3] = {1, 1, 1};
  enc(m, CU_TENSOR_MAP_DATA_TYPE_BFLOAT16, 3, const_cast<void*>(p), dims, str, box, es, CU_TENSOR_MAP_INTERLEAVE_NONE, CU_TENSOR_MAP_SWIZZLE_128B,
      CU_TENSOR_MAP_L2_PROMOTION_L2_256B, CU_TENSOR_MAP_FLOAT_OOB_FILL_NONE);
}

}

extern "C" void kernel_launch(void* const* d_in, const int* in_sizes, int n_in, void* d_out, int out_size) {
  (void)in_sizes; (void)n_in; (void)out_size;
  static EncFn enc = nullptr;
  static void *p_h, *p_u, *p_xb, *p_TI, *p_X1T, *p_ZT, *p_Wt, *p_W0, *p_af, *p_part, *p_gate, *p_flags, *p_epoch;
  if (!enc) {
    void* fn = nullptr;
    cudaDriverEntryPointQueryResult qr;
    cudaGetDriverEntryPoint("cuTensorMapEncodeTiled", &fn, cudaEnableDefault, &qr);
    enc = (EncFn)fn;
    cudaFuncSetAttribute(mega_kernel, cudaFuncAttributeMaxDynamicSharedMemorySize, SM_TOTAL);
    cudaGetSymbolAddress(&p_h, g_h); cudaGetSymbolAddress(&p_u, g_u); cudaGetSymbolAddress(&p_xb, g_xb);
    cudaGetSymbolAddress(&p_TI, g_TI); cudaGetSymbolAddress(&p_Wt, g_Wt); cudaGetSymbolAddress(&p_W0, g_W0);
    cudaGetSymbolAddress(&p_part, g_part);
    cudaGetSymbolAddress(&p_af, g_afrag); cudaGetSymbolAddress(&p_gate, g_gate); cudaGetSymbolAddress(&p_flags, g_flags); cudaGetSymbolAddress(&p_epoch, g_epoch);
    cudaGetSymbolAddress(&p_X1T, g_X1T); cudaGetSymbolAddress(&p_ZT, g_ZT);
  }
  Params P;
  const CUtensorMapSwizzle S128 = CU_TENSOR_MAP_SWIZZLE_128B;
  mk2d(enc, &P.tW1, d_in[4], F_, S_, 64, 64, S128);
  mk2d(enc, &P.tH, p_h, D_, S_, 64, 32, S128);
  mk2d(enc, &P.tW2, d_in[6], S_, F_, 64, 64, S128);
  mk2d(enc, &P.tU, p_u, D_, F_, 64, 64, S128);
  mk2d(enc, &P.tU32, p_u, D_, F_, 64, 32, S128);
  mk2d(enc, &P.tOut, d_out, D_, S_, 32, 64, CU_TENSOR_MAP_SWIZZLE_64B);
  mk2d(enc, &P.tXB, p_xb, 288, 2 * S_, 64, 128, S128, 320);
  mk2d(enc, &P.tTI, p_TI, 576, 288, 64, 96, S128);
  mk2d(enc, &P.tX1s, p_X1T, S_, 576, 64, 144, S128);
  mk3d(enc, &P.tX1c, p_X1T);
  mk3d(enc, &P.tZc, p_ZT);
  mk2d(enc, &P.tZT, p_ZT, S_, 576, 64, 64, S128);
  P.Ax = (const bf16*)d_in[0]; P.Wr = (const bf16*)d_in[1]; P.Wi = (const bf16*)d_in[2];
  P.h = (bf16*)p_h; P.xb = (bf16*)p_xb; P.flags = (unsigned*)p_flags; P.epoch = (unsigned*)p_epoch; P.gate = (float*)p_gate;
  P.Wt = (uint32_t*)p_Wt; P.W0 = (uint2*)p_W0; P.TI = (bf16*)p_TI; P.afrag = (uint4*)p_af; P.part = (uint4*)p_part; P.stamp = nullptr;
  P.b1 = (const bf16*)d_in[5]; P.b2 = (const bf16*)d_in[7]; P.gw = (const bf16*)d_in[8];

  cudaLaunchConfig_t cfg = {};
  cfg.gridDim = dim3(NCTA); cfg.blockDim = dim3(NTHREADS); cfg.dynamicSmemBytes = SM_TOTAL; cfg.stream = cudaStreamPerThread;
  cudaLaunchAttribute at[1];
  at[0].id = cudaLaunchAttributeClusterDimension; at[0].val.clusterDim.x = 2; at[0].val.clusterDim.y = 1; at[0].val.clusterDim.z = 1;
  cfg.attrs = at; cfg.numAttrs = 1;
  cudaLaunchKernelEx(&cfg, mega_kernel, P);
}
```
